```python
import torch

def _softmax(x, axis=-1):
    return torch.softmax(x, dim=axis)
def _gelu(x):
    return torch.nn.functional.gelu(x, approximate="tanh")
def _silu(x):
    return torch.nn.functional.silu(x)
def _sigmoid(x):
    return torch.sigmoid(x)
def _layernorm(x, axis=-1, eps=1e-5):
    m = x.mean(dim=axis, keepdim=True)
    v = x.var(dim=axis, keepdim=True, unbiased=False)
    return (x - m) / torch.sqrt(v + eps)
def _scatter_add(tgt, idx, src, axis=0):
    return tgt.clone().index_add_(axis, idx, src)
def _segment_sum(src, seg, n):
    out = torch.zeros((n,) + src.shape[1:], dtype=src.dtype)
    return out.index_add_(0, seg, src)
def _pad(x, pw):
    flat = tuple(v for pair in reversed(pw) for v in pair)
    return torch.nn.functional.pad(x, flat)

kernel_name = 'recurrent_scan__sliding_local_dilated__moe_arch_mod__prompt'

def setup_inputs():

    _w = (lambda a: (lambda t: t.to(torch.bfloat16) if t.is_floating_point() else t)(torch.as_tensor(a)))
    def _A_setup():
        B, S, D = 1, 2048, 640
        return {
            "x": _w((lambda *s: torch.randn(*s, dtype=torch.bfloat16) * 0.05)(B, S, D)),
            "wqkv": _w((lambda *s: torch.randn(*s, dtype=torch.bfloat16) * 0.05)(D, 3 * D)),
            "wo": _w((lambda *s: torch.randn(*s, dtype=torch.bfloat16) * 0.05)(D, D)),
        }
    _A_in = _A_setup()

    def _B_setup():
        B, S, D, F, C = 1, 2048, 640, 1728, 2
        return {
            "x": _w((lambda *s: torch.randn(*s, dtype=torch.bfloat16) * 0.05)(B, S, D)),
            "w_r": _w((lambda *s: torch.randn(*s, dtype=torch.bfloat16) * 0.05)(D)),
            "w_gate": _w((lambda *s: torch.randn(*s, dtype=torch.bfloat16) * 0.05)(D, F)),
            "w_up": _w((lambda *s: torch.randn(*s, dtype=torch.bfloat16) * 0.05)(D, F)),
            "w_down": _w((lambda *s: torch.randn(*s, dtype=torch.bfloat16) * 0.05)(F, D)),
        }
    _B_in = _B_setup()

    return {
        "A_x": _A_in["x"],
        "A_wqkv": _A_in["wqkv"],
        "A_wo": _A_in["wo"],
        "B_x": _B_in["x"],
        "B_w_r": _B_in["w_r"],
        "B_w_gate": _B_in["w_gate"],
        "B_w_up": _B_in["w_up"],
        "B_w_down": _B_in["w_down"],
    }

def reference(A_x, A_wqkv, A_wo, B_x, B_w_r, B_w_gate, B_w_up, B_w_down):
    def _A_ref(x, wqkv, wo):
        B, S, D = x.shape
        H = 32; Dh = D // H
        W, dil = 8, 2
        qkv = (lambda x, *d: x.permute(*d))((x @ wqkv).reshape(B, S, 3, H, Dh), 2, 0, 3, 1, 4)
        q, k, v = qkv[0], qkv[1], qkv[2]
        scale = Dh ** -0.5
        pos = torch.arange(S)
        off = torch.arange(W) * dil
        idx = pos[:, None] - off[None, :]
        mask = idx >= 0
        idx_c = torch.where(mask, idx, 0).reshape(-1)
        kg = k[:, :, idx_c, :].reshape(B, H, S, W, Dh)
        vg = v[:, :, idx_c, :].reshape(B, H, S, W, Dh)
        logits = torch.einsum("bhsd,bhswd->bhsw", q, kg) * scale
        logits = torch.where(mask[None, None, :, :], logits, -1e9)
        attn = _softmax(logits, axis=-1)
        o = torch.einsum("bhsw,bhswd->bhsd", attn, vg)
        return (lambda x, *d: x.permute(*d))(o, 0, 2, 1, 3).reshape(B, S, D) @ wo

    def _B_ref(x, w_r, w_gate, w_up, w_down):
        B, S, D = x.shape
        C = 2
        r = x @ w_r
        idx = torch.argsort(-r, axis=-1)[:, :C]
        idx_e = (lambda x, n, axis: torch.repeat_interleave(x, n, dim=axis))(idx.reshape(B, C, 1), D, axis=2)
        x_sel = (lambda x, i, axis: torch.take_along_dim(x, i, dim=axis))(x, idx_e, axis=1)
        g = _silu(x_sel @ w_gate)
        u = x_sel @ w_up
        y = (g * u) @ w_down
        r_sel = _sigmoid((lambda x, i, axis: torch.take_along_dim(x, i, dim=axis))(r, idx, axis=1))
        y = y * r_sel.reshape(B, C, 1)
        b_off = (torch.arange(B) * S).reshape(B, 1)
        flat_idx = (idx + b_off).reshape(B * C)
        zero = (x * 0.0).reshape(B * S, D)
        upd = _scatter_add(zero, flat_idx, y.reshape(B * C, D), axis=0)
        return x + upd.reshape(B, S, D)

    x = A_x
    xn = _layernorm(x, axis=-1)
    s = _A_ref(xn, A_wqkv, A_wo)
    g = _silu(_B_ref(xn, B_w_r, B_w_gate, B_w_up, B_w_down))
    return x + s * g
```

```cpp
#include <cuda_runtime.h>
#include <cuda_bf16.h>
#include <cuda.h>
#include <stdint.h>

#define DEVI __device__ __forceinline__

namespace fk {

constexpr int SEQ = 2048, DM = 640, FF = 1728;
constexpr int NCTA = 128, NHELP = 4, NTHREADS = 384;
constexpr int NAUX = 96;
constexpr int NMOE = 108;
constexpr int NMOE_ = 108;
constexpr int STAGE_BYTES = 47104;
constexpr int OFF_B = 16384, B_HALF = 15360;
constexpr int SM_WO = 2 * STAGE_BYTES;
constexpr int SM_BEXT = SM_WO + 102400;
constexpr int SM_ST = SM_BEXT + 7680;
constexpr int SM_YV = SM_ST + 1152;
constexpr int SM_H = SM_YV + 320;
constexpr int SM_GU = SM_H + 128;
constexpr int SM_EARLY = SM_GU + 256;
constexpr int SM_TOP = SM_EARLY + 416;
constexpr int SM_BAR = SM_TOP + 16;
constexpr int SM_XSEL = SM_BAR + 176;
constexpr int SM_EX = SM_XSEL + 5120;
constexpr int SM_TOTAL = SM_EX + 15360;
static_assert(SM_TOTAL <= 232448 && SM_EX % 16 == 0 && SM_BAR % 8 == 0 && SM_XSEL % 16 == 0 && SM_ST % 16 == 0 && SM_YV % 16 == 0, "smem layout");
constexpr int BAR_FULL = 0, BAR_EMPTY = 4, BAR_WO = 8, BAR_XS = 9, BAR_AUX = 10, BAR_Y = 11, BAR_H = 12, BAR_SEL = 13, BAR_O = 14, BAR_GW = 15, BAR_DW = 16, BAR_PX = 17, BAR_GU = 18, BAR_ST = 19;
#define JC 6
#define WPF_MODE 0
#define WPF_KT 3
#define LDO ldg_v4
#define POLL_NS 150
#define GATE_KT 99
#define HELP_DELAY 1u
#define FIN_UNROLL 1
#define ZERO_POS 1
#define O_GI 1
#define PW_NS 32
#define FL_NS 0
#define GW_MODE 0
#define ALAG 1
#define XK0 1
#define EXT_KT 8
#define PF0 4
#define SRC(i) ((i) == 0 ? g : ((i) - 1 < g ? (i) - 1 : (i)))
constexpr unsigned SPIN_MAX = 1u << 21;

struct Scratch {
    uint4 xch[2][NCTA][1600];
    uint4 bext[2][8][480];
    uint4 xmsg[2][192];
    unsigned long long rowinfo[SEQ];
    unsigned keys[SEQ];
    float y[2][DM];
    unsigned epoch[(NCTA + NHELP) * 32];
    unsigned cnt_y[32];
};
__device__ Scratch g_scratch;
#define TL(i) do { } while (0)
#define TLX(i) do { } while (0)
#define TLL(i) do { } while (0)
#define HT(i) do { } while (0)
#define HT_DUMP() do { } while (0)
#define TL_DUMP(role) do { } while (0)

DEVI uint32_t smem_u32(const void* p) { return (uint32_t)__cvta_generic_to_shared(p); }
DEVI void mbar_init(uint32_t bar, uint32_t cnt) { asm volatile("mbarrier.init.shared::cta.b64 [%0], %1;" :: "r"(bar), "r"(cnt)); }
DEVI void mbar_expect_tx(uint32_t bar, uint32_t bytes) { asm volatile("mbarrier.arrive.expect_tx.shared::cta.b64 _, [%0], %1;" :: "r"(bar), "r"(bytes) : "memory"); }
DEVI void mbar_arrive(uint32_t bar) { asm volatile("mbarrier.arrive.shared::cta.b64 _, [%0];" :: "r"(bar) : "memory"); }
DEVI uint32_t clk32() { uint32_t t; asm volatile("mov.u32 %0, %%clock;" : "=r"(t) :: "memory"); return t; }
DEVI bool mbar_try(uint32_t bar, uint32_t parity) {
    uint32_t ok;
    asm volatile("{\n.reg .pred p;\nmbarrier.try_wait.parity.shared::cta.b64 p, [%1], %2, 0x989680;\nselp.u32 %0, 1, 0, p;\n}" : "=r"(ok) : "r"(bar), "r"(parity) : "memory");
    return ok != 0;
}
DEVI void mbar_wait(uint32_t bar, uint32_t parity) {
    while (!mbar_try(bar, parity)) { }
}
DEVI bool elect_one() {
    uint32_t p;
    asm volatile("{\n.reg .pred P;\nelect.sync _|P, 0xffffffff;\nselp.u32 %0, 1, 0, P;\n}" : "=r"(p));
    return p != 0;
}
DEVI void tma3d(uint32_t dst, const CUtensorMap* tm, uint32_t bar, int c0, int c1, int c2) {
    asm volatile("cp.async.bulk.tensor.3d.shared::cluster.global.mbarrier::complete_tx::bytes [%0], [%1, {%3, %4, %5}], [%2];"
                 :: "r"(dst), "l"(tm), "r"(bar), "r"(c0), "r"(c1), "r"(c2) : "memory");
}
DEVI void mbar_wait_spin(uint32_t bar, uint32_t parity) { while (!mbar_try(bar, parity)) { } }
DEVI void tma3d_mc(uint32_t dst, const CUtensorMap* tm, uint32_t bar, int c0, int c1, int c2) {
    asm volatile("cp.async.bulk.tensor.3d.shared::cluster.global.mbarrier::complete_tx::bytes.multicast::cluster [%0], [%1, {%3, %4, %5}], [%2], %6;"
                 :: "r"(dst), "l"(tm), "r"(bar), "r"(c0), "r"(c1), "r"(c2), "h"((uint16_t)3) : "memory");
}
DEVI void tma4d_mc(uint32_t dst, const CUtensorMap* tm, uint32_t bar, int c0, int c1, int c2, int c3) {
    asm volatile("cp.async.bulk.tensor.4d.shared::cluster.global.mbarrier::complete_tx::bytes.multicast::cluster [%0], [%1, {%3, %4, %5, %6}], [%2], %7;"
                 :: "r"(dst), "l"(tm), "r"(bar), "r"(c0), "r"(c1), "r"(c2), "r"(c3), "h"((uint16_t)3) : "memory");
}
DEVI void tma4d(uint32_t dst, const CUtensorMap* tm, uint32_t bar, int c0, int c1, int c2, int c3) {
    asm volatile("cp.async.bulk.tensor.4d.shared::cluster.global.mbarrier::complete_tx::bytes [%0], [%1, {%3, %4, %5, %6}], [%2];"
                 :: "r"(dst), "l"(tm), "r"(bar), "r"(c0), "r"(c1), "r"(c2), "r"(c3) : "memory");
}
DEVI void mbar_arrive_both(uint32_t bar) {
    asm volatile("{\n.reg .b32 ra;\nmapa.shared::cluster.u32 ra, %0, 0;\nmbarrier.arrive.shared::cluster.b64 _, [ra];\n"
                 "mapa.shared::cluster.u32 ra, %0, 1;\nmbarrier.arrive.shared::cluster.b64 _, [ra];\n}" :: "r"(bar) : "memory");
}
DEVI void st_async_peer(uint32_t addr, uint32_t bar, uint32_t peer, uint32_t v) {
    asm volatile("{\n.reg .b32 ra, rb;\nmapa.shared::cluster.u32 ra, %0, %2;\nmapa.shared::cluster.u32 rb, %1, %2;\n"
                 "st.async.weak.shared::cluster.mbarrier::complete_tx::bytes.b32 [ra], %3, [rb];\n}" :: "r"(addr), "r"(bar), "r"(peer), "r"(v) : "memory");
}
DEVI void tma3d_store(const CUtensorMap* tm, uint32_t src, int c0, int c1, int c2) {
    asm volatile("cp.async.bulk.tensor.3d.global.shared::cta.bulk_group [%0, {%2, %3, %4}], [%1];"
                 :: "l"(tm), "r"(src), "r"(c0), "r"(c1), "r"(c2) : "memory");
}
DEVI void prefetch_tmap(const CUtensorMap* tm) { asm volatile("prefetch.tensormap [%0];" :: "l"(tm) : "memory"); }
DEVI void bulk_load(uint32_t dst, const void* src, uint32_t bytes, uint32_t bar) {
    asm volatile("cp.async.bulk.shared::cluster.global.mbarrier::complete_tx::bytes [%0], [%1], %2, [%3];" :: "r"(dst), "l"(src), "r"(bytes), "r"(bar) : "memory");
}
DEVI void prefetch_l2_bulk(const void* p, uint32_t bytes) { asm volatile("cp.async.bulk.prefetch.L2.global [%0], %1;" :: "l"(p), "r"(bytes) : "memory"); }
DEVI void wg_fence() { asm volatile("wgmma.fence.sync.aligned;" ::: "memory"); }
DEVI void wg_commit() { asm volatile("wgmma.commit_group.sync.aligned;" ::: "memory"); }
template <int N> DEVI void wg_wait() { asm volatile("wgmma.wait_group.sync.aligned %0;" :: "n"(N) : "memory"); }
template <int ID, int N> DEVI void bar_sync() { asm volatile("bar.sync %0, %1;" :: "n"(ID), "n"(N) : "memory"); }
DEVI void spin_guard(unsigned& n) { if (++n > SPIN_MAX) __trap(); }
DEVI uint4 ld_relaxed_v4(const void* p) {
    uint4 v;
    asm volatile("ld.relaxed.gpu.global.v4.u32 {%0,%1,%2,%3}, [%4];" : "=r"(v.x), "=r"(v.y), "=r"(v.z), "=r"(v.w) : "l"(p) : "memory");
    return v;
}
DEVI void st_relaxed_v4(void* p, const uint4& v) {
    asm volatile("st.relaxed.gpu.global.v4.u32 [%0], {%1,%2,%3,%4};" :: "l"(p), "r"(v.x), "r"(v.y), "r"(v.z), "r"(v.w) : "memory");
}
DEVI unsigned ld_relaxed_u32(const void* p) { unsigned v; asm volatile("ld.relaxed.gpu.global.u32 %0, [%1];" : "=r"(v) : "l"(p) : "memory"); return v; }
DEVI unsigned ld_acquire_u32(const void* p) { unsigned v; asm volatile("ld.acquire.gpu.global.u32 %0, [%1];" : "=r"(v) : "l"(p) : "memory"); return v; }
DEVI float ld_relaxed_f32(const void* p) { float v; asm volatile("ld.relaxed.gpu.global.f32 %0, [%1];" : "=f"(v) : "l"(p) : "memory"); return v; }
DEVI void st_relaxed_u64(void* p, unsigned long long v) { asm volatile("st.relaxed.gpu.global.u64 [%0], %1;" :: "l"(p), "l"(v) : "memory"); }
DEVI void st_release_u32(void* p, unsigned v) { asm volatile("st.release.gpu.global.u32 [%0], %1;" :: "l"(p), "r"(v) : "memory"); }
DEVI uint4 ld_gen_v4(const void* p) {
    uint4 v;
    asm volatile("ld.relaxed.gpu.v4.u32 {%0,%1,%2,%3}, [%4];" : "=r"(v.x), "=r"(v.y), "=r"(v.z), "=r"(v.w) : "l"(p) : "memory");
    return v;
}
DEVI void st_gen_v4(void* p, const uint4& v) { asm volatile("st.relaxed.gpu.v4.u32 [%0], {%1,%2,%3,%4};" :: "l"(p), "r"(v.x), "r"(v.y), "r"(v.z), "r"(v.w) : "memory"); }
DEVI void poll_word(const void* p) {
    unsigned spins = 0;
    while (ld_relaxed_u32(p) == 0) { __nanosleep(PW_NS); if (++spins > SPIN_MAX) __trap(); }
}
DEVI void wait_counter(const unsigned* p, unsigned target) {
    unsigned spins = 0;
    while ((int)(ld_acquire_u32(p) - target) < 0) { __nanosleep(64); if (++spins > SPIN_MAX) __trap(); }
}
DEVI float sqrt_approx(float x) { float y; asm("sqrt.approx.ftz.f32 %0, %1;" : "=f"(y) : "f"(x)); return y; }
DEVI void red_add_u32(unsigned* p, unsigned v) { asm volatile("red.relaxed.gpu.global.add.u32 [%0], %1;" :: "l"(p), "r"(v) : "memory"); }
DEVI void fence_gpu() { asm volatile("fence.acq_rel.gpu;" ::: "memory"); }
DEVI void red_release_add(unsigned* p, unsigned v) { asm volatile("red.release.gpu.global.add.u32 [%0], %1;" :: "l"(p), "r"(v) : "memory"); }
DEVI void red_add_v4(float* p, float a, float b, float c, float d) {
    asm volatile("red.relaxed.gpu.global.add.v4.f32 [%0], {%1,%2,%3,%4};" :: "l"(p), "f"(a), "f"(b), "f"(c), "f"(d) : "memory");
}
DEVI uint4 ldg_v4(const void* p) {
    uint4 v;
    asm volatile("ld.global.v4.u32 {%0,%1,%2,%3}, [%4];" : "=r"(v.x), "=r"(v.y), "=r"(v.z), "=r"(v.w) : "l"(p) : "memory");
    return v;
}
DEVI uint4 lds_v4(uint32_t a) { uint4 v; asm volatile("ld.shared.v4.u32 {%0,%1,%2,%3}, [%4];" : "=r"(v.x), "=r"(v.y), "=r"(v.z), "=r"(v.w) : "r"(a)); return v; }
DEVI void sts_v4(uint32_t a, const uint4& v) { asm volatile("st.shared.v4.u32 [%0], {%1,%2,%3,%4};" :: "r"(a), "r"(v.x), "r"(v.y), "r"(v.z), "r"(v.w) : "memory"); }
DEVI float2 lds_f2(uint32_t a) { float2 v; asm volatile("ld.shared.v2.f32 {%0,%1}, [%2];" : "=f"(v.x), "=f"(v.y) : "r"(a)); return v; }
DEVI void ldsm4(uint32_t addr, uint32_t& a, uint32_t& b, uint32_t& c, uint32_t& d) {
    asm volatile("ldmatrix.sync.aligned.m8n8.x4.shared.b16 {%0,%1,%2,%3}, [%4];" : "=r"(a), "=r"(b), "=r"(c), "=r"(d) : "r"(addr));
}
DEVI void stsm4(uint32_t addr, uint32_t a, uint32_t b, uint32_t c, uint32_t d) {
    asm volatile("stmatrix.sync.aligned.m8n8.x4.shared.b16 [%0], {%1,%2,%3,%4};" :: "r"(addr), "r"(a), "r"(b), "r"(c), "r"(d) : "memory");
}
DEVI uint32_t movm(uint32_t a) { uint32_t d; asm("movmatrix.sync.aligned.m8n8.trans.b16 %0, %1;" : "=r"(d) : "r"(a)); return d; }
DEVI void mma16(float (&c)[4], uint32_t a0, uint32_t a1, uint32_t a2, uint32_t a3, uint32_t b0, uint32_t b1) {
    asm("mma.sync.aligned.m16n8k16.row.col.f32.bf16.bf16.f32 {%0,%1,%2,%3}, {%4,%5,%6,%7}, {%8,%9}, {%0,%1,%2,%3};"
                 : "+f"(c[0]), "+f"(c[1]), "+f"(c[2]), "+f"(c[3]) : "r"(a0), "r"(a1), "r"(a2), "r"(a3), "r"(b0), "r"(b1));
}
DEVI void mma8(float (&c)[4], uint32_t a0, uint32_t a1, uint32_t b0) {
    asm("mma.sync.aligned.m16n8k8.row.col.f32.bf16.bf16.f32 {%0,%1,%2,%3}, {%4,%5}, {%6}, {%0,%1,%2,%3};"
                 : "+f"(c[0]), "+f"(c[1]), "+f"(c[2]), "+f"(c[3]) : "r"(a0), "r"(a1), "r"(b0));
}
DEVI uint32_t pack_bf16(float lo, float hi) { uint32_t d; asm("cvt.rn.bf16x2.f32 %0, %1, %2;" : "=r"(d) : "f"(hi), "f"(lo)); return d; }
DEVI float bf_lo(uint32_t v) { return __uint_as_float(v << 16); }
DEVI float bf_hi(uint32_t v) { return __uint_as_float(v & 0xffff0000u); }
DEVI float bfr(float x) { return __bfloat162float(__float2bfloat16_rn(x)); }
DEVI uint32_t nz(uint32_t w) { uint32_t d; asm("max.u32 %0, %1, 1;" : "=r"(d) : "r"(w)); return d; }
DEVI float ex2(float x) { float y; asm("ex2.approx.ftz.f32 %0, %1;" : "=f"(y) : "f"(x)); return y; }
DEVI float rcp(float x) { float y; asm("rcp.approx.ftz.f32 %0, %1;" : "=f"(y) : "f"(x)); return y; }
DEVI float sigmoid_f(float x) { return rcp(1.0f + ex2(x * -1.4426950408889634f)); }
DEVI float silu_f(float x) { const float h = 0.5f * x; float t; asm("tanh.approx.f32 %0, %1;" : "=f"(t) : "f"(h)); return fmaf(h, t, h); }
DEVI uint32_t hsub2(uint32_t a, uint32_t b) { uint32_t d; asm("sub.rn.bf16x2 %0, %1, %2;" : "=r"(d) : "r"(a), "r"(b)); return d; }
DEVI uint32_t hadd2(uint32_t a, uint32_t b) { uint32_t d; asm("add.rn.bf16x2 %0, %1, %2;" : "=r"(d) : "r"(a), "r"(b)); return d; }
DEVI uint32_t hmul2(uint32_t a, uint32_t b) { uint32_t d; asm("mul.rn.bf16x2 %0, %1, %2;" : "=r"(d) : "r"(a), "r"(b)); return d; }
DEVI uint32_t dup_hi(float x) { return __byte_perm(__float_as_uint(x), 0, 0x3232); }
DEVI uint2 ldg_v2(const void* p) { uint2 v; asm volatile("ld.global.v2.u32 {%0,%1}, [%2];" : "=r"(v.x), "=r"(v.y) : "l"(p) : "memory"); return v; }
DEVI void sts_u16(uint32_t a, uint32_t v) { asm volatile("st.shared.u16 [%0], %1;" :: "r"(a), "h"((unsigned short)v) : "memory"); }
DEVI void sts_u32(uint32_t a, uint32_t v) { asm volatile("st.shared.u32 [%0], %1;" :: "r"(a), "r"(v) : "memory"); }
DEVI void sts_f2(uint32_t a, float x, float y) { asm volatile("st.shared.v2.f32 [%0], {%1,%2};" :: "r"(a), "f"(x), "f"(y) : "memory"); }
DEVI uint2 lds_v2(uint32_t a) { uint2 v; asm volatile("ld.shared.v2.u32 {%0,%1}, [%2];" : "=r"(v.x), "=r"(v.y) : "r"(a)); return v; }
DEVI uint32_t lds_u32(uint32_t a) { uint32_t v; asm volatile("ld.shared.u32 %0, [%1];" : "=r"(v) : "r"(a)); return v; }
DEVI float lds_f32(uint32_t a) { float v; asm volatile("ld.shared.f32 %0, [%1];" : "=f"(v) : "r"(a)); return v; }
DEVI void st_relaxed_u32(void* p, unsigned v) { asm volatile("st.relaxed.gpu.global.u32 [%0], %1;" :: "l"(p), "r"(v) : "memory"); }
DEVI unsigned long long ld_relaxed_u64(const void* p) { unsigned long long v; asm volatile("ld.relaxed.gpu.global.u64 %0, [%1];" : "=l"(v) : "l"(p) : "memory"); return v; }

DEVI void wgmma_rs_n192(float (&d)[120], uint32_t a0, uint32_t a1, uint32_t a2, uint32_t a3, uint32_t blo, uint32_t scale_d) {
    asm volatile("{\n.reg .b64 db;\n.reg .pred p;\n"
        "setp.ne.b32 p, %101, 0;\n"
        "mov.b64 db, {%100, 0x40000040};\n"
        "wgmma.mma_async.sync.aligned.m64n192k16.f32.bf16.bf16 "
        "{%0, %1, %2, %3, %4, %5, %6, %7, %8, %9, %10, %11, %12, %13, %14, %15, %16, %17, %18, %19, %20, %21, %22, %23, %24, %25, %26, %27, %28, %29, %30, %31, %32, %33, %34, %35, %36, %37, %38, %39, %40, %41, %42, %43, %44, %45, %46, %47, %48, %49, %50, %51, %52, %53, %54, %55, %56, %57, %58, %59, %60, %61, %62, %63, %64, %65, %66, %67, %68, %69, %70, %71, %72, %73, %74, %75, %76, %77, %78, %79, %80, %81, %82, %83, %84, %85, %86, %87, %88, %89, %90, %91, %92, %93, %94, %95}, "
        "{%96, %97, %98, %99}, db, p, 1, 1, 1;\n}\n"
        : "+f"(d[0]), "+f"(d[1]), "+f"(d[2]), "+f"(d[3]), "+f"(d[4]), "+f"(d[5]), "+f"(d[6]), "+f"(d[7]), "+f"(d[8]), "+f"(d[9]), "+f"(d[10]), "+f"(d[11]), "+f"(d[12]), "+f"(d[13]), "+f"(d[14]), "+f"(d[15]), "+f"(d[16]), "+f"(d[17]), "+f"(d[18]), "+f"(d[19]), "+f"(d[20]), "+f"(d[21]), "+f"(d[22]), "+f"(d[23]), "+f"(d[24]), "+f"(d[25]), "+f"(d[26]), "+f"(d[27]), "+f"(d[28]), "+f"(d[29]), "+f"(d[30]), "+f"(d[31]), "+f"(d[32]), "+f"(d[33]), "+f"(d[34]), "+f"(d[35]), "+f"(d[36]), "+f"(d[37]), "+f"(d[38]), "+f"(d[39]), "+f"(d[40]), "+f"(d[41]), "+f"(d[42]), "+f"(d[43]), "+f"(d[44]), "+f"(d[45]), "+f"(d[46]), "+f"(d[47]), "+f"(d[48]), "+f"(d[49]), "+f"(d[50]), "+f"(d[51]), "+f"(d[52]), "+f"(d[53]), "+f"(d[54]), "+f"(d[55]), "+f"(d[56]), "+f"(d[57]), "+f"(d[58]), "+f"(d[59]), "+f"(d[60]), "+f"(d[61]), "+f"(d[62]), "+f"(d[63]), "+f"(d[64]), "+f"(d[65]), "+f"(d[66]), "+f"(d[67]), "+f"(d[68]), "+f"(d[69]), "+f"(d[70]), "+f"(d[71]), "+f"(d[72]), "+f"(d[73]), "+f"(d[74]), "+f"(d[75]), "+f"(d[76]), "+f"(d[77]), "+f"(d[78]), "+f"(d[79]), "+f"(d[80]), "+f"(d[81]), "+f"(d[82]), "+f"(d[83]), "+f"(d[84]), "+f"(d[85]), "+f"(d[86]), "+f"(d[87]), "+f"(d[88]), "+f"(d[89]), "+f"(d[90]), "+f"(d[91]), "+f"(d[92]), "+f"(d[93]), "+f"(d[94]), "+f"(d[95])
        : "r"(a0), "r"(a1), "r"(a2), "r"(a3), "r"(blo), "r"(scale_d));
}
DEVI void wgmma_rs_n48(float (&d)[120], uint32_t a0, uint32_t a1, uint32_t a2, uint32_t a3, uint32_t blo, uint32_t scale_d) {
    asm volatile("{\n.reg .b64 db;\n.reg .pred p;\n"
        "setp.ne.b32 p, %29, 0;\n"
        "mov.b64 db, {%28, 0xc0000010};\n"
        "wgmma.mma_async.sync.aligned.m64n48k16.f32.bf16.bf16 "
        "{%0, %1, %2, %3, %4, %5, %6, %7, %8, %9, %10, %11, %12, %13, %14, %15, %16, %17, %18, %19, %20, %21, %22, %23}, "
        "{%24, %25, %26, %27}, db, p, 1, 1, 1;\n}\n"
        : "+f"(d[96]), "+f"(d[97]), "+f"(d[98]), "+f"(d[99]), "+f"(d[100]), "+f"(d[101]), "+f"(d[102]), "+f"(d[103]), "+f"(d[104]), "+f"(d[105]), "+f"(d[106]), "+f"(d[107]), "+f"(d[108]), "+f"(d[109]), "+f"(d[110]), "+f"(d[111]), "+f"(d[112]), "+f"(d[113]), "+f"(d[114]), "+f"(d[115]), "+f"(d[116]), "+f"(d[117]), "+f"(d[118]), "+f"(d[119])
        : "r"(a0), "r"(a1), "r"(a2), "r"(a3), "r"(blo), "r"(scale_d));
}
DEVI void wgmma_rs_n64(float (&d)[40], uint32_t a0, uint32_t a1, uint32_t a2, uint32_t a3, uint32_t blo) {
    asm volatile("{\n.reg .b64 db;\n.reg .pred p;\n"
        "mov.b64 db, {%36, 0x40000040};\n"
        "wgmma.mma_async.sync.aligned.m64n64k16.f32.bf16.bf16 "
        "{%0, %1, %2, %3, %4, %5, %6, %7, %8, %9, %10, %11, %12, %13, %14, %15, %16, %17, %18, %19, %20, %21, %22, %23, %24, %25, %26, %27, %28, %29, %30, %31}, "
        "{%32, %33, %34, %35}, db, 1, 1, 1, 1;\n}\n"
        : "+f"(d[0]), "+f"(d[1]), "+f"(d[2]), "+f"(d[3]), "+f"(d[4]), "+f"(d[5]), "+f"(d[6]), "+f"(d[7]), "+f"(d[8]), "+f"(d[9]), "+f"(d[10]), "+f"(d[11]), "+f"(d[12]), "+f"(d[13]), "+f"(d[14]), "+f"(d[15]), "+f"(d[16]), "+f"(d[17]), "+f"(d[18]), "+f"(d[19]), "+f"(d[20]), "+f"(d[21]), "+f"(d[22]), "+f"(d[23]), "+f"(d[24]), "+f"(d[25]), "+f"(d[26]), "+f"(d[27]), "+f"(d[28]), "+f"(d[29]), "+f"(d[30]), "+f"(d[31])
        : "r"(a0), "r"(a1), "r"(a2), "r"(a3), "r"(blo));
}
DEVI void wgmma_rs_n16(float (&d)[40], uint32_t a0, uint32_t a1, uint32_t a2, uint32_t a3, uint32_t blo) {
    asm volatile("{\n.reg .b64 db;\n.reg .pred p;\n"
        "mov.b64 db, {%12, 0xc0000010};\n"
        "wgmma.mma_async.sync.aligned.m64n16k16.f32.bf16.bf16 "
        "{%0, %1, %2, %3, %4, %5, %6, %7}, "
        "{%8, %9, %10, %11}, db, 1, 1, 1, 1;\n}\n"
        : "+f"(d[32]), "+f"(d[33]), "+f"(d[34]), "+f"(d[35]), "+f"(d[36]), "+f"(d[37]), "+f"(d[38]), "+f"(d[39])
        : "r"(a0), "r"(a1), "r"(a2), "r"(a3), "r"(blo));
}

DEVI void helper_cta(Scratch* __restrict__ sc, const __nv_bfloat16* __restrict__ x, const CUtensorMap* tm_cs, uint32_t sb, int cta) {
    const int warp = threadIdx.x >> 5, lane = threadIdx.x & 31, h = cta - NCTA;
    constexpr int RING = 6, BOX = 32768;
    const uint32_t hb = sb + RING * BOX;
    const int a0 = h < 3 ? 8 * h : 23;
    if (threadIdx.x == 0) {
#pragma unroll
        for (int s = 0; s < RING; s++) { mbar_init(hb + s * 8, 1); mbar_init(hb + (RING + s) * 8, 8); }
        asm volatile("fence.mbarrier_init.release.cluster;" ::: "memory");
    }
    __syncthreads();
    if (warp == 8) {
        if (lane == 0) {
            { const uint32_t t0 = clk32(); while (clk32() - t0 < HELP_DELAY) __nanosleep(100); }
            int s = 0, ph = 1;
#pragma unroll 1
            for (int it = 0; it < 2 * JC; it++) {
                mbar_wait(hb + (RING + s) * 8, ph);
                mbar_expect_tx(hb + s * 8, BOX); tma3d(sb + s * BOX, tm_cs, hb + s * 8, 0, it * 32, a0);
                if (++s == RING) { s = 0; ph ^= 1; }
            }
        }
        return;
    }
    if (warp < 8) {
        const unsigned epoch = ld_relaxed_u32(&sc->epoch[cta * 32]);
        const int t = threadIdx.x;
        float cs[8];
#pragma unroll
        for (int e = 0; e < 8; e++) cs[e] = 0.f;
        const uint32_t off = ((t >> 3) & 7) * 4096 + (t & 7) * 16 + (t >> 6) * 1024;
        int s = 0, ph = 0;
#pragma unroll 1
        for (int it = 0; it < 2 * JC; it++) {
            mbar_wait(hb + s * 8, ph);
            uint4 v[8];
#pragma unroll
            for (int j = 0; j < 8; j++) v[j] = lds_v4(sb + s * BOX + off + j * 128);
#pragma unroll
            for (int j = 0; j < 8; j++) {
                const uint32_t* u = &v[j].x;
#pragma unroll
                for (int e = 0; e < 4; e++) { cs[2 * e] += bf_lo(u[e]); cs[2 * e + 1] += bf_hi(u[e]); }
            }
            __syncwarp();
            if (lane == 0) mbar_arrive(hb + (RING + s) * 8);
            if (++s == RING) { s = 0; ph ^= 1; }
        }
        bar_sync<2, 256>();
        if (t == 0) HT(0);
        sts_v4(sb + t * 32, make_uint4(__float_as_uint(cs[0]), __float_as_uint(cs[1]), __float_as_uint(cs[2]), __float_as_uint(cs[3])));
        sts_v4(sb + t * 32 + 16, make_uint4(__float_as_uint(cs[4]), __float_as_uint(cs[5]), __float_as_uint(cs[6]), __float_as_uint(cs[7])));
        bar_sync<2, 256>();
        const int col8 = a0 * 8 + t;
        if (t < (h < 2 ? 64 : 56)) {
#pragma unroll
            for (int e = 0; e < 8; e++) cs[e] = (lds_f32(sb + t * 32 + e * 4) + lds_f32(sb + (t + 64) * 32 + e * 4)) + (lds_f32(sb + (t + 128) * 32 + e * 4) + lds_f32(sb + (t + 192) * 32 + e * 4));
            const int part = col8 / 80, g = (col8 % 80) / 10, c8 = col8 % 10;
            const bool mainp = c8 < 8;
            char* base = reinterpret_cast<char*>(&sc->bext[epoch & 1][g][0]) + (mainp ? part * 2048 : 6144 + part * 512);
#pragma unroll
            for (int kr = 0; kr < 3; kr++) {
                uint32_t o[4];
#pragma unroll
                for (int e = 0; e < 4; e++) { o[e] = pack_bf16(cs[2 * e], cs[2 * e + 1]); cs[2 * e] -= bf_lo(o[e]); cs[2 * e + 1] -= bf_hi(o[e]); }
                const int off = mainp ? kr * 128 + ((c8 ^ kr) << 4) : kr * 32 + ((c8 - 8) << 4);
                st_relaxed_v4(base + off, make_uint4(nz(o[0]), nz(o[1]), nz(o[2]), nz(o[3])));
                *reinterpret_cast<uint4*>(base + off + (1 - 2 * (int)(epoch & 1)) * (int)sizeof(sc->bext[0])) = make_uint4(0, 0, 0, 0);
            }
        }
        if (t == 0 && h) { st_relaxed_u32(&sc->epoch[cta * 32], epoch + 1); HT(1); HT_DUMP(); }
        return;
    }
    if (h) return;
    const int t = threadIdx.x - 288;
#pragma unroll 1
    for (int i = t; i < 320; i += 96) reinterpret_cast<uint4*>(&sc->y[0][0])[i] = make_uint4(0, 0, 0, 0);
    if (t < 8) reinterpret_cast<uint4*>(sc->cnt_y)[t] = make_uint4(0, 0, 0, 0);
    const unsigned epoch = ld_relaxed_u32(&sc->epoch[cta * 32]);
    const unsigned tag = epoch + 1;
    sc->xmsg[(epoch & 1) ^ 1][t] = sc->xmsg[(epoch & 1) ^ 1][t + 96] = make_uint4(0, 0, 0, 0);
    fence_gpu();
    unsigned k1 = 0, k2 = 0;
    {
        uint4 kq[6];
        unsigned spins = 0;
        while (true) {
            unsigned bad = 0;
#pragma unroll
            for (int j = 0; j < 6; j++) {
                kq[j] = ld_relaxed_v4(reinterpret_cast<const uint4*>(sc->keys) + min(t + 96 * j, 511));
                bad |= ((kq[j].x ^ tag) | (kq[j].y ^ tag) | (kq[j].z ^ tag) | (kq[j].w ^ tag)) & 31;
            }
            if (!bad) break;
            __nanosleep(64);
            spin_guard(spins);
        }
        HT(0);
#pragma unroll
        for (int j = 0; j < 6; j++) {
            const uint32_t* u = &kq[j].x;
#pragma unroll
            for (int e = 0; e < 4; e++) { const unsigned kk = (j == 5 && t >= 32) ? 0u : u[e]; k2 = max(k2, min(k1, kk)); k1 = max(k1, kk); }
        }
#pragma unroll
        for (int o = 1; o < 32; o <<= 1) {
            const unsigned o1 = __shfl_xor_sync(0xffffffffu, k1, o), o2 = __shfl_xor_sync(0xffffffffu, k2, o);
            k2 = max(min(k1, o1), max(k2, o2)); k1 = max(k1, o1);
        }
        if (lane == 0) { sts_u32(sb + 200000 + (warp - 9) * 8, k1); sts_u32(sb + 200000 + (warp - 9) * 8 + 4, k2); }
        bar_sync<1, 96>();
        k1 = k2 = 0;
#pragma unroll
        for (int q = 0; q < 6; q++) { const unsigned kk = lds_u32(sb + 200000 + q * 4); k2 = max(k2, min(k1, kk)); k1 = max(k1, kk); }
    }
    const int sel0 = 2047 - ((k1 >> 5) & 2047), sel1 = 2047 - ((k2 >> 5) & 2047);
    HT(1);
    if (t < 80) {
        const uint4 v0 = ldg_v4(reinterpret_cast<const uint4*>(x + sel0 * DM) + t), v1 = ldg_v4(reinterpret_cast<const uint4*>(x + sel1 * DM) + t);
        unsigned long long i0, i1; unsigned spins = 0;
        while (true) {
            i0 = ld_relaxed_u64(&sc->rowinfo[sel0]); i1 = ld_relaxed_u64(&sc->rowinfo[sel1]);
            if ((unsigned)(i0 >> 32) == tag && (unsigned)(i1 >> 32) == tag) break;
            spin_guard(spins);
        }
        uint32_t xn[2][4];
#pragma unroll
        for (int tk = 0; tk < 2; tk++) {
            const unsigned info = (unsigned)(tk ? i1 : i0);
            const uint32_t m2 = __byte_perm(info, 0, 0x1010);
            const float rs = 1.0f / bf_hi(info);
            const uint32_t* u = tk ? &v1.x : &v0.x;
#pragma unroll
            for (int e = 0; e < 4; e++) { const uint32_t d = hsub2(u[e], m2); xn[tk][e] = pack_bf16(bf_lo(d) * rs, bf_hi(d) * rs); }
        }
        uint4* dst = &sc->xmsg[epoch & 1][2 * t];
        st_relaxed_v4(dst, make_uint4(nz(__byte_perm(xn[0][0], xn[1][0], 0x5410)), nz(__byte_perm(xn[0][0], xn[1][0], 0x7632)),
                                      nz(__byte_perm(xn[0][1], xn[1][1], 0x5410)), nz(__byte_perm(xn[0][1], xn[1][1], 0x7632))));
        st_relaxed_v4(dst + 1, make_uint4(nz(__byte_perm(xn[0][2], xn[1][2], 0x5410)), nz(__byte_perm(xn[0][2], xn[1][2], 0x7632)),
                                          nz(__byte_perm(xn[0][3], xn[1][3], 0x5410)), nz(__byte_perm(xn[0][3], xn[1][3], 0x7632))));
    }
    if (t == 80) st_relaxed_v4(&sc->xmsg[epoch & 1][160], make_uint4((1u << 30) | (sel0 << 11) | sel1, k1, k2, 1));
    if (t == 0) { st_relaxed_u32(&sc->epoch[cta * 32], tag); HT(2);
        HT_DUMP(); }
}

__global__ void __cluster_dims__(2, 1, 1) __launch_bounds__(NTHREADS, 1) fused_kernel(
    Scratch* __restrict__ sc,
    const __nv_bfloat16* __restrict__ x, const __nv_bfloat16* __restrict__ wqkv, const __nv_bfloat16* __restrict__ wo,
    const __nv_bfloat16* __restrict__ wr, const __nv_bfloat16* __restrict__ wg, const __nv_bfloat16* __restrict__ wu,
    const __nv_bfloat16* __restrict__ wd, __nv_bfloat16* __restrict__ out,
    const __grid_constant__ CUtensorMap tm_x, const __grid_constant__ CUtensorMap tm_w, const __grid_constant__ CUtensorMap tm_wt,
    const __grid_constant__ CUtensorMap tm_wo, const __grid_constant__ CUtensorMap tm_wot, const __grid_constant__ CUtensorMap tm_xs, const __grid_constant__ CUtensorMap tm_cs,
    const __grid_constant__ CUtensorMap tm_g, const __grid_constant__ CUtensorMap tm_u)
{
    extern __shared__ __align__(1024) unsigned char smem[];
    uint32_t sb;
    asm volatile("mov.u32 %0, %1;" : "=r"(sb) : "r"(smem_u32(smem)));
    unsigned cta, nsm;
    asm("mov.u32 %0, %%smid;" : "=r"(cta)); asm("mov.u32 %0, %%nsmid;" : "=r"(nsm));
    {
        const unsigned t = cta >> 1, u = t - 32, q = (u * 37) >> 8;
        const unsigned pi = t < 32 ? (t & 7) * 8 + (t >> 3) : (t < 60 ? (1 + u - 7 * q) * 8 + 4 + q : (t < 62 ? t + 4 : t - 58));
        cta = nsm == NCTA + NHELP ? pi * 2 + (blockIdx.x & 1) : blockIdx.x;
    }
    if (cta >= NCTA) { helper_cta(sc, x, &tm_cs, sb, cta); return; }
    const int warp = __shfl_sync(0xffffffffu, threadIdx.x >> 5, 0), lane = threadIdx.x & 31;
    const int pidx = cta >> 1;
    const int m = (pidx >> 3) * 2 + (cta & 1), g = pidx & 7;
    const uint32_t bars = sb + SM_BAR;

    if (warp == 9) {
        const __nv_bfloat16* xr = x + (m * 128 + g * 16) * DM;
        if (lane < 16 * XK0) asm volatile("prefetch.global.L2 [%0];" :: "l"(xr + (lane & 15) * DM + (lane >> 4) * 64));
        __syncwarp();
        if (lane == 0) prefetch_l2_bulk(xr, 16 * DM * 2);
    }
    if (warp == 8) {
        if (elect_one()) {
            prefetch_tmap(&tm_x); prefetch_tmap(&tm_w); prefetch_tmap(&tm_wt);
#pragma unroll
            for (int s = 0; s < 20; s++) mbar_init(bars + s * 8, (s >> 2) == 1 ? 4 : (s == BAR_O ? 8 : (s == BAR_H ? 2 : 1)));
            asm volatile("fence.mbarrier_init.release.cluster;" ::: "memory");
        }
        __syncwarp();
    }
    asm volatile("barrier.cluster.arrive.relaxed.aligned;\nbarrier.cluster.wait.aligned;" ::: "memory");
    __syncthreads();
    if (threadIdx.x == 0) TL(8);

    if (warp >= 8) {
        asm volatile("setmaxnreg.dec.sync.aligned.u32 104;");
        if (warp == 8) {
#pragma unroll 1
            for (int kt = 0; kt < 10; kt++) {
                const int s = kt & 3;
                if (kt >= 4) mbar_wait(bars + (BAR_EMPTY + s) * 8, ((kt >> 2) - 1) & 1);
                if (elect_one()) {
                    const uint32_t fb = bars + (BAR_FULL + s) * 8, st = sb + s * STAGE_BYTES;
                    mbar_expect_tx(fb, STAGE_BYTES);
                    const int hf = cta & 1;
                    tma3d_mc(st + OFF_B + hf * B_HALF, &tm_w, fb, g * 80, kt * 64 + hf * 32, 0);
                    tma3d(st + OFF_B + 12288, &tm_wt, fb, g * 80 + 64, kt * 64, 0); tma3d(st + OFF_B + B_HALF + 12288, &tm_wt, fb, g * 80 + 64, kt * 64 + 32, 0);
                    for (int ka = kt < 4 ? kt - ALAG : kt; ka <= (kt == 3 ? 3 : (kt < 4 ? kt - ALAG : kt)); ka++)
                        if (ka >= 0) tma3d(sb + (ka & 3) * STAGE_BYTES, &tm_x, bars + (BAR_FULL + (ka & 3)) * 8, ka * 64, m * 64, 0);
                    if (WPF_MODE == 3 && kt == WPF_KT) prefetch_l2_bulk(wqkv + (256 + cta * 3) * 1920, 3 * 1920 * 2);
                    if (kt >= PF0) {
                        const int j = kt - PF0;
                        if (j < 4) prefetch_l2_bulk(reinterpret_cast<const char*>(j & 1 ? wu : wg) + cta * 17280 + (j >> 1) * 8640, 8640);
                        else prefetch_l2_bulk(reinterpret_cast<const char*>(wd) + cta * 17280 + (j - 4) * 8640, 8640);
                        if (j == 1) prefetch_l2_bulk(reinterpret_cast<const char*>(wo) + cta * 6400, 6400);
                    }
                    if (kt == 0) TL(17);
                    if (kt == 3) TL(18);
                }
                __syncwarp();
            }
            if (lane == 0) TL(16);
            if (elect_one()) mbar_expect_tx(bars + BAR_WO * 8, 102400);
#pragma unroll 1
            for (int ph = 0; ph < 2; ph++) {
                mbar_wait(bars + (BAR_EMPTY + 2 + ph) * 8, 1);
                if (elect_one()) {
#pragma unroll 1
                    for (int q = ph * 5 + ((ph * 5 ^ cta) & 1); q < ph * 5 + 5; q += 2) tma3d_mc(sb + SM_WO + q * 8192, &tm_wo, bars + BAR_WO * 8, g * 80, q * 64, 0);
                }
                __syncwarp();
            }
            if (cta < NMOE) {
                mbar_wait(bars + BAR_EMPTY * 8, 0);
                if (elect_one()) {
                    mbar_expect_tx(bars + BAR_GW * 8, 640 * 64);
#pragma unroll 1
                    for (int j = 0; j < 5; j++) tma3d(sb + j * 8192, (cta & 1) ? &tm_u : &tm_g, bars + BAR_GW * 8, (cta >> 1) * 32, j * 128, 0);
                }
                __syncwarp();
            }
            mbar_wait(bars + BAR_H * 8, 0);
            mbar_wait(bars + (BAR_EMPTY + 1) * 8, 0);
            if (elect_one()) {
#pragma unroll 1
                for (int q = cta & 1; q < 5; q += 2) tma3d_mc(sb + SM_WO + 81920 + q * 4096, &tm_wot, bars + BAR_WO * 8, g * 80 + 64, q * 128, 0);
                if (cta < NMOE) {
                    mbar_expect_tx(bars + BAR_DW * 8, 16 * DM * 2);
                    bulk_load(sb + STAGE_BYTES + 20480, wd + cta * 16 * DM, 16 * DM * 2, bars + BAR_DW * 8);
                }
            }
            __syncwarp();
            mbar_wait(bars + BAR_O * 8, 0);
            if (elect_one()) {
                mbar_expect_tx(bars + BAR_XS * 8, 20480);
                tma3d(sb + STAGE_BYTES, &tm_xs, bars + BAR_XS * 8, g * 80, m * 64, 0);
                TL_DUMP(2);
            }
            __syncwarp();
        } else {
            const int ta = threadIdx.x - 288, wa = warp - 9, q1 = ta < 48 ? ta + 96 : ta;
            const unsigned epoch = ld_relaxed_u32(&sc->epoch[cta * 32]);
            const unsigned long long *r0 = &sc->rowinfo[max(m * 128 - 16 + ta, 0)], *r1 = &sc->rowinfo[max(m * 128 - 16 + q1, 0)];
            unsigned long long v0 = ld_relaxed_u64(r0), v1 = ld_relaxed_u64(r1);
            const uint32_t scr = sb + SM_XSEL;
#pragma unroll 1
            for (int i = ta; i < 480; i += NAUX) sts_v4(sb + SM_BEXT + i * 16, make_uint4(0, 0, 0, 0));
            asm volatile("fence.proxy.async.shared::cta;" ::: "memory");
            const unsigned tag = epoch + 1;
            {
                unsigned spins = 0;
                while ((unsigned)(v0 >> 32) != tag || (unsigned)(v1 >> 32) != tag) {
                    __nanosleep(POLL_NS); spin_guard(spins);
                    v0 = ld_relaxed_u64(r0); v1 = ld_relaxed_u64(r1);
                }
                sts_f2(sb + SM_ST + ((ta & 1) * 72 + (ta >> 1)) * 8, bf_lo((unsigned)v0), rcp(bf_hi((unsigned)v0)));
                if (ta < 48) sts_f2(sb + SM_ST + ((q1 & 1) * 72 + (q1 >> 1)) * 8, bf_lo((unsigned)v1), rcp(bf_hi((unsigned)v1)));
            }
            bar_sync<3, NAUX>();
            if (ta == 0) { mbar_arrive(bars + BAR_ST * 8); TLX(11); }
            {
                const uint4* xch = &sc->xch[epoch & 1][m * 8][0];
                if (ta < 64 && (ta & 7) < 7) sts_u32(sb + SM_EARLY + ta * 4, ld_relaxed_u32(xch + ((g + 1 + (ta & 7)) & 7) * 1600 + (ta >> 3) * 160 + 128));
                if (ta < 2) sts_u32(sb + SM_EARLY + 256 + ta * 4, ld_relaxed_u32(xch + (g - (m > 0 ? 8 : 0)) * 1600 + 1280 + ta * 160 + 128));
            }
            {
                const int off = ta < 72 ? (ta / 24) * 128 + ta % 24 : 384 + ((min(ta, 89) - 72) / 6) * 32 + (min(ta, 89) - 72) % 6;
                const uint4* img = &sc->bext[epoch & 1][g][off];
                uint4 v; unsigned spins = 0;
                while ((v = ld_relaxed_v4(img)).x == 0) { __nanosleep(POLL_NS); spin_guard(spins); }
                sts_v4(sb + SM_BEXT + off * 16, v);
                asm volatile("fence.proxy.async.shared::cta;" ::: "memory");
                bar_sync<3, NAUX>();
                if (ta == 0) { mbar_arrive(bars + BAR_AUX * 8); TLX(12); }
            }
            const bool moe = cta < NMOE;
            if (ta == 1) mbar_expect_tx(bars + BAR_PX * 8, 128);
            {
                const uint4* msg = &sc->xmsg[epoch & 1][0];
                const int c1 = min(ta + 96, 160);
                if (ta == 0) { unsigned spins = 0; while (ld_relaxed_u32(msg + 160) == 0) { __nanosleep(POLL_NS); spin_guard(spins); } }
                bar_sync<3, NAUX>();
                uint4 a, bb; unsigned spins = 0;
                while (true) {
                    a = ld_relaxed_v4(msg + ta); bb = ld_relaxed_v4(msg + c1);
                    if (a.x != 0 && bb.x != 0) break;
                    spin_guard(spins);
                }
                sts_v4(scr + ta * 32, make_uint4(a.x << 16, a.x & 0xffff0000u, a.y << 16, a.y & 0xffff0000u));
                sts_v4(scr + ta * 32 + 16, make_uint4(a.z << 16, a.z & 0xffff0000u, a.w << 16, a.w & 0xffff0000u));
                if (c1 < 160) {
                    sts_v4(scr + c1 * 32, make_uint4(bb.x << 16, bb.x & 0xffff0000u, bb.y << 16, bb.y & 0xffff0000u));
                    sts_v4(scr + c1 * 32 + 16, make_uint4(bb.z << 16, bb.z & 0xffff0000u, bb.w << 16, bb.w & 0xffff0000u));
                } else if (ta == 64) sts_v4(sb + SM_TOP, bb);
            }
            bar_sync<3, NAUX>();
            if (ta == 0) { mbar_arrive(bars + BAR_SEL * 8); TLX(20); }
            if (moe) {
                const int tq = ta < 80 ? ta : ta - 16;
                uint32_t wa_ = sb + tq * 16, xs = scr + (tq >> 2) * 8, xstride = 160;
                int n4 = 8;
                mbar_wait(bars + BAR_GW * 8, 0);
#pragma unroll 1
                for (int phase = 0; phase < 2; phase++) {
                    float a0[8], a1[8];
#pragma unroll
                    for (int e = 0; e < 8; e++) { a0[e] = 0.f; a1[e] = 0.f; }
#pragma unroll 1
                    for (int b = 0; b < n4; b++) {
                        uint4 v[4]; float2 xv[4];
#pragma unroll
                        for (int j = 0; j < 4; j++) { v[j] = lds_v4(wa_); wa_ += 1280; xv[j] = lds_f2(xs); xs += xstride; }
#pragma unroll
                        for (int j = 0; j < 4; j++) {
                            const uint32_t* u = &v[j].x;
#pragma unroll
                            for (int e = 0; e < 4; e++) {
                                const float wl = bf_lo(u[e]), wh = bf_hi(u[e]);
                                a0[2 * e] = fmaf(xv[j].x, wl, a0[2 * e]); a0[2 * e + 1] = fmaf(xv[j].x, wh, a0[2 * e + 1]);
                                a1[2 * e] = fmaf(xv[j].y, wl, a1[2 * e]); a1[2 * e + 1] = fmaf(xv[j].y, wh, a1[2 * e + 1]);
                            }
                        }
                    }
                    if (phase == 1) {
                        if (ta == 0) TLX(22);
                        if (ta < 80) {
                            sts_v4(scr + ta * 32, make_uint4(__float_as_uint(a0[0]), __float_as_uint(a0[1]), __float_as_uint(a0[2]), __float_as_uint(a0[3])));
                            sts_v4(scr + ta * 32 + 16, make_uint4(__float_as_uint(a0[4]), __float_as_uint(a0[5]), __float_as_uint(a0[6]), __float_as_uint(a0[7])));
                            sts_v4(scr + 2560 + ta * 32, make_uint4(__float_as_uint(a1[0]), __float_as_uint(a1[1]), __float_as_uint(a1[2]), __float_as_uint(a1[3])));
                            sts_v4(scr + 2560 + ta * 32 + 16, make_uint4(__float_as_uint(a1[4]), __float_as_uint(a1[5]), __float_as_uint(a1[6]), __float_as_uint(a1[7])));
                        }
                        asm volatile("fence.proxy.async.shared::cta;" ::: "memory");
                        bar_sync<3, NAUX>();
                        if (ta == 0) {
                            asm volatile("cp.reduce.async.bulk.global.shared::cta.bulk_group.add.f32 [%0], [%1], 5120;\n"
                                         "cp.async.bulk.commit_group;\ncp.async.bulk.wait_group 0;" :: "l"(&sc->y[0][0]), "r"(scr) : "memory");
                            red_add_u32(&sc->cnt_y[0], 1);
                        }
                        break;
                    }
                    if (ta == 0) TLX(21);
                    bar_sync<3, NAUX>();
                    if (ta == 0) mbar_arrive(bars + BAR_GU * 8);
                    if (ta < 80) {
                        const uint32_t dst = scr + ta * 64;
                        sts_v4(dst, make_uint4(__float_as_uint(a0[0]), __float_as_uint(a0[1]), __float_as_uint(a0[2]), __float_as_uint(a0[3])));
                        sts_v4(dst + 16, make_uint4(__float_as_uint(a0[4]), __float_as_uint(a0[5]), __float_as_uint(a0[6]), __float_as_uint(a0[7])));
                        sts_v4(dst + 32, make_uint4(__float_as_uint(a1[0]), __float_as_uint(a1[1]), __float_as_uint(a1[2]), __float_as_uint(a1[3])));
                        sts_v4(dst + 48, make_uint4(__float_as_uint(a1[4]), __float_as_uint(a1[5]), __float_as_uint(a1[6]), __float_as_uint(a1[7])));
                    }
                    bar_sync<3, NAUX>();
                    if (ta < 64) {
                        float sum = 0.f;
#pragma unroll 5
                        for (int q = 0; q < 20; q++) sum += lds_f32(scr + q * 256 + ta * 4);
                        const uint32_t slot = ((((ta >> 4) & 1) * 8 + (ta & 7)) * 2 + ((ta >> 3) & 1)) * 4, val = __float_as_uint(bfr(sum));
                        if ((ta >> 5) == (cta & 1)) sts_u32(sb + SM_GU + slot, val);
                        else st_async_peer(sb + SM_GU + 128 + slot, bars + BAR_PX * 8, (cta & 1) ^ 1, val);
                    }
                    bar_sync<3, NAUX>();
                    mbar_wait(bars + BAR_PX * 8, 0);
                    if (ta < 32) {
                        const float own = lds_f32(sb + SM_GU + ta * 4), oth = lds_f32(sb + SM_GU + 128 + ta * 4);
                        const float gs = (cta & 1) ? oth : own, us = (cta & 1) ? own : oth;
                        sts_u32(sb + SM_H + ta * 4, __float_as_uint(bfr(bfr(gs * sigmoid_f(gs)) * us)));
                    }
                    mbar_wait(bars + BAR_DW * 8, 0);
                    bar_sync<3, NAUX>();
                    wa_ = sb + STAGE_BYTES + 20480 + tq * 16; xs = sb + SM_H; xstride = 8; n4 = 4;
                }
            } else if (ta == 0) mbar_arrive(bars + BAR_GU * 8);
            if (ta == 0) TLL(13);
            if (wa == 0) {
                const uint4 rec = lds_v4(sb + SM_TOP);
                if (((rec.x >> 18) & 15) == m || ((rec.x >> 7) & 15) == m) {
                    if (lane == 0) wait_counter(&sc->cnt_y[0], NMOE);
                    __syncwarp();
                    if (lane < 20) {
                        const int tk = lane >= 10;
                        const uint32_t ks = (tk ? rec.z : rec.y) >> 16;
                        const float sg = bfr(sigmoid_f(__uint_as_float(((ks & 0x8000u) ? (ks & 0x7fffu) : (ks ^ 0xffffu)) << 16)));
                        const float* src = &sc->y[tk][g * 80 + (lane - tk * 10) * 8];
                        const uint4 ya = ld_relaxed_v4(src), yb = ld_relaxed_v4(src + 4);
                        sts_v4(sb + SM_YV + lane * 16,
                               make_uint4(pack_bf16(bfr(__uint_as_float(ya.x)) * sg, bfr(__uint_as_float(ya.y)) * sg), pack_bf16(bfr(__uint_as_float(ya.z)) * sg, bfr(__uint_as_float(ya.w)) * sg),
                                          pack_bf16(bfr(__uint_as_float(yb.x)) * sg, bfr(__uint_as_float(yb.y)) * sg), pack_bf16(bfr(__uint_as_float(yb.z)) * sg, bfr(__uint_as_float(yb.w)) * sg)));
                    }
                    __syncwarp();
                }
                if (lane == 0) { mbar_arrive(bars + BAR_Y * 8); TLL(14); TL_DUMP(1); }
            }
#pragma unroll 1
            for (int i = ta; i < 1600; i += NAUX) sc->xch[(epoch & 1) ^ 1][m * 8 + g][i] = make_uint4(0, 0, 0, 0);
        }
    } else {
        asm volatile("setmaxnreg.inc.sync.aligned.u32 200;");
        const int p = warp >> 2, w = warp & 3, c = lane & 3, r = lane >> 2;
        const unsigned epoch = ld_relaxed_u32(&sc->epoch[cta * 32]);
        {
            const __nv_bfloat16* xr = x + (m * 128 + g * 16 + 2 * warp) * DM;
            uint2 xv[5], xw[5], wv[5]; uint32_t pvb[2];
#pragma unroll
            for (int j = 0; j < 5; j++) {
                xv[j] = ldg_v2(reinterpret_cast<const uint2*>(xr) + lane + 32 * j);
                xw[j] = ldg_v2(reinterpret_cast<const uint2*>(xr + DM) + lane + 32 * j);
                wv[j] = ldg_v2(reinterpret_cast<const uint2*>(wr) + lane + 32 * j);
            }
            pvb[0] = *reinterpret_cast<const unsigned short*>(xr); pvb[1] = *reinterpret_cast<const unsigned short*>(xr + DM);
            __syncwarp();
            float wf[20], wsum = 0.f;
#pragma unroll
            for (int j = 0; j < 5; j++) {
                wf[4 * j] = bf_lo(wv[j].x); wf[4 * j + 1] = bf_hi(wv[j].x); wf[4 * j + 2] = bf_lo(wv[j].y); wf[4 * j + 3] = bf_hi(wv[j].y);
                wsum += (wf[4 * j] + wf[4 * j + 1]) + (wf[4 * j + 2] + wf[4 * j + 3]);
            }
#pragma unroll
            for (int o = 1; o < 32; o <<= 1) wsum += __shfl_xor_sync(0xffffffffu, wsum, o);
            float t1 = 0.f, t2 = 0.f, t3 = 0.f, tp = 0.f;
#pragma unroll 1
            for (int q = 0; q < 2; q++) {
                const float pv = __uint_as_float(pvb[0] << 16);
                pvb[0] = pvb[1];
                float s1[2] = {0.f, 0.f}, s2[2] = {0.f, 0.f}, s3[2] = {0.f, 0.f};
#pragma unroll
                for (int j = 0; j < 5; j++) {
                    const float a4[4] = {bf_lo(xv[j].x) - pv, bf_hi(xv[j].x) - pv, bf_lo(xv[j].y) - pv, bf_hi(xv[j].y) - pv};
#pragma unroll
                    for (int e = 0; e < 4; e++) { s1[e & 1] += a4[e]; s2[e & 1] = fmaf(a4[e], a4[e], s2[e & 1]); s3[e & 1] = fmaf(a4[e], wf[4 * j + e], s3[e & 1]); }
                    xv[j] = xw[j];
                }
                const float u1 = s1[0] + s1[1], u2 = s2[0] + s2[1], u3 = s3[0] + s3[1];
                const float o1 = u1 + __shfl_xor_sync(0xffffffffu, u1, 1), o2 = u2 + __shfl_xor_sync(0xffffffffu, u2, 1), o3 = u3 + __shfl_xor_sync(0xffffffffu, u3, 1);
                if ((lane & 1) == q) { t1 = o1; t2 = o2; t3 = o3; tp = pv; }
            }
#pragma unroll
            for (int o = 2; o < 32; o <<= 1) {
                t1 += __shfl_xor_sync(0xffffffffu, t1, o); t2 += __shfl_xor_sync(0xffffffffu, t2, o); t3 += __shfl_xor_sync(0xffffffffu, t3, o);
            }
            if (lane < 2) {
                const int row = m * 128 + g * 16 + 2 * warp + lane;
                const float d = t1 * (1.0f / DM);
                const float mb = bfr(tp + d);
                const float sd = bfr(sqrt_approx(bfr(bfr(fmaxf(fmaf(-d, d, t2 * (1.0f / DM)), 0.f)) + 1e-5f)));
                const uint32_t u = __float_as_uint(bfr(fmaf(tp - mb, wsum, t3) * rcp(sd))) >> 16;
                const unsigned tag = epoch + 1;
                st_relaxed_u64(&sc->rowinfo[row], (unsigned long long)((__float_as_uint(mb) >> 16) | (__float_as_uint(sd) & 0xffff0000u)) | ((unsigned long long)tag << 32));
                st_relaxed_u32(&sc->keys[row], (((u & 0x8000u) ? (u ^ 0xffffu) : (u | 0x8000u)) << 16) | ((2047 - row) << 5) | (tag & 31));
            }
            if (threadIdx.x == 0) TL(7);
                                }
        uint4* const xch = &sc->xch[epoch & 1][m * 8][0];
        const uint32_t stb = sb + SM_ST + (p * 72 + w * 16) * 8;
        float acc[120];
#pragma unroll
        for (int i = 0; i < 120; i++) asm volatile("" : "=f"(acc[i]));
        {
            uint32_t m0 = 0, m1 = 0;
            const int lr = w * 16 + (lane & 15);
            const uint32_t a_off = p * 8192 + lr * 128, a_x = lr & 7, a_h = lane >> 4;
            const uint32_t blo = (((sb + OFF_B) & 0x3ffffu) >> 4) | ((4096u >> 4) << 16);
            const uint32_t tlo = (((sb + OFF_B + 12288) & 0x3ffffu) >> 4) | ((1024u >> 4) << 16);
            uint32_t af[2][8];
#pragma unroll 1
            for (int kt = 0; kt < 10; kt++) {
                const int s = kt & 3;
                mbar_wait(bars + (BAR_FULL + s) * 8, (kt >> 2) & 1);
                if (kt == 0 && threadIdx.x == 0) TL(1);
                if (kt == JC) {
                    mbar_wait(bars + BAR_ST * 8, 0);
                    m0 = dup_hi(lds_f32(stb + (8 + r) * 8)); m1 = dup_hi(lds_f32(stb + (16 + r) * 8));
                    if (threadIdx.x == 0) TL(10);
                }
                const uint32_t st = sb + s * STAGE_BYTES + a_off, so = s * (STAGE_BYTES >> 4);
#pragma unroll
                for (int u = 0; u < 2; u++) {
#pragma unroll
                    for (int k = 0; k < 2; k++) {
                        ldsm4(st + (((4 * u + 2 * k + a_h) ^ a_x) << 4), af[u][4 * k], af[u][4 * k + 1], af[u][4 * k + 2], af[u][4 * k + 3]);
                        af[u][4 * k] = hsub2(af[u][4 * k], m0); af[u][4 * k + 1] = hsub2(af[u][4 * k + 1], m1);
                        af[u][4 * k + 2] = hsub2(af[u][4 * k + 2], m0); af[u][4 * k + 3] = hsub2(af[u][4 * k + 3], m1);
                    }
                    wg_fence();
#pragma unroll
                    for (int k = 0; k < 2; k++) {
                        const uint32_t sd = (u | k) ? 1u : (uint32_t)kt;
                        wgmma_rs_n192(acc, af[u][4 * k], af[u][4 * k + 1], af[u][4 * k + 2], af[u][4 * k + 3], blo + so + u * (B_HALF >> 4) + k * 128, sd);
                        wgmma_rs_n48(acc, af[u][4 * k], af[u][4 * k + 1], af[u][4 * k + 2], af[u][4 * k + 3], tlo + so + u * (B_HALF >> 4) + k * 32, sd);
                    }
                    wg_commit();
                    wg_wait<1>();
                    if (u == 0 && kt > 0 && (threadIdx.x & 127) == 0) mbar_arrive_both(bars + (BAR_EMPTY + ((kt - 1) & 3)) * 8);
                }
                if (kt == EXT_KT) {
                    mbar_wait(bars + BAR_AUX * 8, 0);
                    const uint32_t msk = c == 0 ? 0xffffffffu : (c == 1 ? 0x0000ffffu : 0u);
                    const uint32_t e0 = (m0 ^ 0x80008000u) & msk, e1 = (m1 ^ 0x80008000u) & msk;
                    wg_fence();
                    wgmma_rs_n192(acc, e0, e1, 0u, 0u, (((sb + SM_BEXT) & 0x3ffffu) >> 4) | ((2048u >> 4) << 16), 1u);
                    wgmma_rs_n48(acc, e0, e1, 0u, 0u, (((sb + SM_BEXT + 6144) & 0x3ffffu) >> 4) | ((512u >> 4) << 16), 1u);
                    wg_commit();
                    wg_wait<0>();
                }
            }
        }
        unsigned early = lane < 7 ? lds_u32(sb + SM_EARLY + warp * 32 + lane * 4) : 0u;
        const bool halo_seen = lds_u32(sb + SM_EARLY + 256 + p * 4) != 0;
        const float2 st0 = lds_f2(stb + (8 + r) * 8), st1 = lds_f2(stb + (16 + r) * 8);
        const uint4 sP = lds_v4(stb + (2 * c) * 8), sB = lds_v4(stb + (8 + 2 * c) * 8), sC = lds_v4(stb + (16 + 2 * c) * 8);
        const bool up0 = 2 * c > r, up1 = 2 * c + 1 > r;
        const float k00 = __uint_as_float(up0 ? sP.y : sB.y), k01 = __uint_as_float(up1 ? sP.w : sB.w);
        const float k10 = __uint_as_float(up0 ? sB.y : sC.y), k11 = __uint_as_float(up1 ? sB.w : sC.w);
        const float sc2 = 0.22360679774997896f * 1.4426950408889634f;
        const float f00 = st0.y * k00 * sc2, f01 = st0.y * k01 * sc2, f10 = st1.y * k10 * sc2, f11 = st1.y * k11 * sc2;
        const bool first = (m == 0 && w == 0);
        const float b00 = (first && up0) ? -1e30f : 0.f, b01 = (first && up1) ? -1e30f : 0.f;
        const uint32_t mup = (up0 ? 0x0000ffffu : 0u) | (up1 ? 0xffff0000u : 0u);
        uint4* const exs = reinterpret_cast<uint4*>(smem + SM_EX) + p * 480 + lane;
        uint4* hdst = w == 3 ? xch + g * 1600 + 1280 + p * 160 + lane : exs + w * 160;
        const uint4* hsrc = w > 0 ? exs + (w - 1) * 160 : (m > 0 ? xch + (g - 8) * 1600 + 1280 + p * 160 + lane : exs);
        uint4* ob = xch + warp * 160 + lane;
        uint4* ob_own = ob + g * 1600;
        const uint4* flagp = ob - lane + ((g + 1 + min(lane, 6)) & 7) * 1600 + 128;
        asm volatile("" : "+l"(hdst), "+l"(hsrc), "+l"(ob), "+l"(ob_own), "+l"(flagp));
        wg_wait<0>();
        if ((threadIdx.x & 127) == 0) mbar_arrive_both(bars + (BAR_EMPTY + 1) * 8);
        if (threadIdx.x == 0) TL(2);
        uint32_t Q[10][2], K[10][2], V[10][2], Kp[10], Vp[10];
#pragma unroll
        for (int b = 0; b < 10; b++) {
            const int jk = b < 8 ? 8 + b : 18 + b, jv = b < 8 ? 16 + b : 20 + b;
            V[b][1] = nz(movm(pack_bf16(acc[4 * jv + 2], acc[4 * jv + 3])));
            K[b][1] = nz(pack_bf16(acc[4 * jk + 2], acc[4 * jk + 3]));
        }
        st_gen_v4(hdst, make_uint4(K[0][1], K[1][1], K[2][1], K[3][1])); st_gen_v4(hdst + 32, make_uint4(K[4][1], K[5][1], K[6][1], K[7][1]));
        st_gen_v4(hdst + 64, make_uint4(K[8][1], K[9][1], V[0][1], V[1][1])); st_gen_v4(hdst + 96, make_uint4(V[2][1], V[3][1], V[4][1], V[5][1]));
        st_gen_v4(hdst + 128, make_uint4(V[6][1], V[7][1], V[8][1], V[9][1]));
        __syncwarp();
#pragma unroll
        for (int b = 0; b < 10; b++) {
            const int jq = b < 8 ? b : 16 + b, jk = b < 8 ? 8 + b : 18 + b, jv = b < 8 ? 16 + b : 20 + b;
            V[b][0] = movm(pack_bf16(acc[4 * jv], acc[4 * jv + 1]));
            K[b][0] = pack_bf16(acc[4 * jk], acc[4 * jk + 1]);
            Q[b][0] = pack_bf16(acc[4 * jq], acc[4 * jq + 1]); Q[b][1] = pack_bf16(acc[4 * jq + 2], acc[4 * jq + 3]);
        }
        {
            if (threadIdx.x == 0) TLX(23);
            if (p == 0) bar_sync<1, 128>(); else bar_sync<2, 128>();
            if (threadIdx.x == 0) TLX(24);
            const uint4* src = hsrc;
            uint4 rcv[5];
            unsigned spins = 0;
            while (true) {
                if (w == 0 && m > 0 && !halo_seen) poll_word(src + 128 - lane);
#pragma unroll
                for (int i = 0; i < 5; i++) rcv[i] = ld_gen_v4(src + i * 32);
                const unsigned mn = min(min(min(rcv[0].x, rcv[1].x), min(rcv[2].x, rcv[3].x)), rcv[4].x);
                if (__all_sync(0xffffffffu, mn != 0)) break;
                spin_guard(spins);
            }
            Kp[0] = rcv[0].x; Kp[1] = rcv[0].y; Kp[2] = rcv[0].z; Kp[3] = rcv[0].w; Kp[4] = rcv[1].x; Kp[5] = rcv[1].y; Kp[6] = rcv[1].z; Kp[7] = rcv[1].w;
            Kp[8] = rcv[2].x; Kp[9] = rcv[2].y; Vp[0] = rcv[2].z; Vp[1] = rcv[2].w; Vp[2] = rcv[3].x; Vp[3] = rcv[3].y; Vp[4] = rcv[3].z; Vp[5] = rcv[3].w;
            Vp[6] = rcv[4].x; Vp[7] = rcv[4].y; Vp[8] = rcv[4].z; Vp[9] = rcv[4].w;
        }
        if (w == 0 && lane == 0) mbar_arrive(bars + BAR_H * 8);
        if (threadIdx.x == 0) TL(3);
        if (threadIdx.x == 32) TLX(27);
        uint32_t of[10][2];
#pragma unroll 1
        for (int hp = 0; hp < 2; hp++) {
            float sp[2][4], sm_[2][4], sc[2][4], O[5][4];
#pragma unroll
            for (int b = 0; b < 5; b++) { O[b][0] = O[b][1] = O[b][2] = O[b][3] = 0.f; }
#pragma unroll
            for (int h = 0; h < 2; h++) {
                const int bx = 3 * h, by = bx + 1;
                const bool qmine = h ? (c >= 2) : (c < 2);
                const uint32_t qz0 = qmine ? Q[2][0] : 0u, qz1 = qmine ? Q[2][1] : 0u;
#pragma unroll
                for (int e = 0; e < 4; e++) { sp[h][e] = 0.f; sm_[h][e] = 0.f; sc[h][e] = 0.f; }
                mma16(sm_[h], Q[bx][0], Q[bx][1], Q[by][0], Q[by][1], K[bx][0], K[by][0]);
                mma16(sc[h], Q[bx][0], Q[bx][1], Q[by][0], Q[by][1], K[bx][1], K[by][1]);
                mma16(sp[h], Q[bx][0], Q[bx][1], Q[by][0], Q[by][1], Kp[bx], Kp[by]);
                mma8(sm_[h], qz0, qz1, K[2][0]); mma8(sc[h], qz0, qz1, K[2][1]); mma8(sp[h], qz0, qz1, Kp[2]);
            }
            float l[2][4], mx[2][2];
#pragma unroll
            for (int h = 0; h < 2; h++) {
                l[h][0] = fmaf(up0 ? sp[h][0] : sm_[h][0], f00, b00); l[h][1] = fmaf(up1 ? sp[h][1] : sm_[h][1], f01, b01);
                l[h][2] = (up0 ? sm_[h][2] : sc[h][2]) * f10; l[h][3] = (up1 ? sm_[h][3] : sc[h][3]) * f11;
                mx[h][0] = fmaxf(l[h][0], l[h][1]); mx[h][1] = fmaxf(l[h][2], l[h][3]);
            }
#pragma unroll
            for (int o = 1; o < 4; o <<= 1) {
#pragma unroll
                for (int h = 0; h < 2; h++) { mx[h][0] = fmaxf(mx[h][0], __shfl_xor_sync(0xffffffffu, mx[h][0], o)); mx[h][1] = fmaxf(mx[h][1], __shfl_xor_sync(0xffffffffu, mx[h][1], o)); }
            }
            float sum[2][2];
#pragma unroll
            for (int h = 0; h < 2; h++) {
                l[h][0] = ex2(l[h][0] - mx[h][0]); l[h][1] = ex2(l[h][1] - mx[h][0]); l[h][2] = ex2(l[h][2] - mx[h][1]); l[h][3] = ex2(l[h][3] - mx[h][1]);
                sum[h][0] = l[h][0] + l[h][1]; sum[h][1] = l[h][2] + l[h][3];
            }
#pragma unroll
            for (int o = 1; o < 4; o <<= 1) {
#pragma unroll
                for (int h = 0; h < 2; h++) { sum[h][0] += __shfl_xor_sync(0xffffffffu, sum[h][0], o); sum[h][1] += __shfl_xor_sync(0xffffffffu, sum[h][1], o); }
            }
#pragma unroll
            for (int h = 0; h < 2; h++) {
                const int bx = 3 * h, by = bx + 1;
                const float i0 = rcp(sum[h][0]), i1 = rcp(sum[h][1]);
                const uint32_t pl = pack_bf16(l[h][0] * i0 * k00, l[h][1] * i0 * k01), ph = pack_bf16(l[h][2] * i1 * k10, l[h][3] * i1 * k11);
                const uint32_t a0 = pl & mup, a2 = pl & ~mup, a3 = ph & mup, c1 = ph & ~mup;
                const bool vmine = h ? (r >= 4) : (r < 4);
                mma16(O[bx], a0, 0u, a2, a3, Vp[bx], V[bx][0]);
                mma16(O[by], a0, 0u, a2, a3, Vp[by], V[by][0]);
                mma16(O[2], a0, 0u, a2, a3, vmine ? Vp[2] : 0u, vmine ? V[2][0] : 0u);
                mma8(O[bx], 0u, c1, V[bx][1]); mma8(O[by], 0u, c1, V[by][1]); mma8(O[2], 0u, c1, vmine ? V[2][1] : 0u);
            }
#pragma unroll
            for (int b = 0; b < 5; b++) {
                of[b][0] = of[b + 5][0]; of[b][1] = of[b + 5][1];
                of[b + 5][0] = nz(pack_bf16(O[b][0], O[b][1])); of[b + 5][1] = nz(pack_bf16(O[b][2], O[b][3]));
                Q[b][0] = Q[b + 5][0]; Q[b][1] = Q[b + 5][1]; K[b][0] = K[b + 5][0]; K[b][1] = K[b + 5][1];
                V[b][0] = V[b + 5][0]; V[b][1] = V[b + 5][1]; Kp[b] = Kp[b + 5]; Vp[b] = Vp[b + 5];
            }
        }
        uint4 fr[4][5];
#pragma unroll
        for (int d = 1; d < 4; d++) {
#pragma unroll
            for (int t = 0; t < 5; t++) asm volatile("" : "=r"(fr[d][t].x), "=r"(fr[d][t].y), "=r"(fr[d][t].z), "=r"(fr[d][t].w));
        }
#pragma unroll
        for (int t = 0; t < 5; t++) { fr[0][t] = make_uint4(of[2 * t][0], of[2 * t][1], of[2 * t + 1][0], of[2 * t + 1][1]); st_relaxed_v4(ob_own + t * 32, fr[0][t]); }
        if (O_GI < 0 && lane == 0) mbar_arrive(bars + BAR_O * 8);
        if (threadIdx.x == 0) TL(4);
        float acc2[40];
#pragma unroll
        for (int i = 0; i < 40; i++) acc2[i] = 0.f;
        mbar_wait(bars + BAR_WO * 8, 0);
        const uint32_t wlo = (((sb + SM_WO) & 0x3ffffu) >> 4) | (1u << 16), wtlo = (((sb + SM_WO + 81920) & 0x3ffffu) >> 4) | (1u << 16);
#pragma unroll 1
        for (int it = 0; it < 2; it++) {
#pragma unroll
            for (int q = 0; q < 4; q++) {
                const int gi = it * 4 + q, gg = SRC(gi);
                unsigned retries = 0;
                while (true) {
                    const unsigned mn = min(min(min(fr[q][0].x, fr[q][1].x), min(fr[q][2].x, fr[q][3].x)), fr[q][4].x);
                    if (__all_sync(0xffffffffu, mn != 0)) break;
                    spin_guard(retries);
#pragma unroll
                    for (int t = 0; t < 5; t++) fr[q][t] = ld_relaxed_v4(ob + gg * 1600 + t * 32);
                }
                wg_fence();
#pragma unroll
                for (int t = 0; t < 5; t++) {
                    wgmma_rs_n64(acc2, fr[q][t].x, fr[q][t].y, fr[q][t].z, fr[q][t].w, wlo + (gg * 5 + t) * 128);
                    wgmma_rs_n16(acc2, fr[q][t].x, fr[q][t].y, fr[q][t].z, fr[q][t].w, wtlo + (gg * 5 + t) * 32);
                }
                wg_commit();
                if (gi == O_GI && lane == 0) mbar_arrive(bars + BAR_O * 8);
                if (gi == 0) {
                    unsigned spins = 0;
                    while (!__all_sync(0xffffffffu, early != 0 || lane > 6)) { if (FL_NS) __nanosleep(FL_NS); early = ld_relaxed_u32(flagp); spin_guard(spins); }
#pragma unroll
                    for (int d = 1; d < 4; d++) {
#pragma unroll
                        for (int t = 0; t < 5; t++) fr[d][t] = LDO(ob + SRC(d) * 1600 + t * 32);
                    }
                    __syncwarp();
                }
                wg_wait<1>();
                if (gi >= 1 && gi <= 4) {
#pragma unroll
                    for (int t = 0; t < 5; t++) fr[(q + 3) & 3][t] = LDO(ob + SRC(gi + 3) * 1600 + t * 32);
                    __syncwarp();
                }
            }
        }
        wg_wait<0>();
        if (threadIdx.x == 0) TL(5);
        mbar_wait(bars + BAR_XS * 8, 0);
        mbar_wait(bars + BAR_GU * 8, 0);
        const uint32_t ssb = sb + p * 10240 + w * 2560, xsb = ssb + STAGE_BYTES;
        {
            const uint32_t laddr = ssb + ((lane & 7) + ((lane >> 3) & 1) * 8) * 160 + (lane >> 4) * 16;
#pragma unroll
            for (int t = 0; t < 5; t++)
                stsm4(laddr + t * 32, pack_bf16(acc2[8 * t], acc2[8 * t + 1]), pack_bf16(acc2[8 * t + 2], acc2[8 * t + 3]),
                      pack_bf16(acc2[8 * t + 4], acc2[8 * t + 5]), pack_bf16(acc2[8 * t + 6], acc2[8 * t + 7]));
        }
        mbar_wait(bars + BAR_SEL * 8, 0);
        __syncwarp();
        const unsigned selrec = lds_u32(sb + SM_TOP);
        const int sel0 = (selrec >> 11) & 2047, sel1 = selrec & 2047;
        const int wrow = m * 128 + 32 * w + p;
        const bool anysel = ((unsigned)(sel0 - wrow) < 32u && !((sel0 ^ wrow) & 1)) || ((unsigned)(sel1 - wrow) < 32u && !((sel1 ^ wrow) & 1));
#pragma unroll 1
        for (int pass = 0; pass < 2; pass++) {
            if (pass) { if (!anysel) break; mbar_wait(bars + BAR_Y * 8, 0); }
#pragma unroll 1
            for (int t = 0; t < 5; t++) {
                const int idx = t * 32 + lane, row = idx / 10, ch = idx - row * 10;
                const uint4 xv = lds_v4(xsb + idx * 16), sv = lds_v4(ssb + idx * 16);
                const float2 st = lds_f2(stb + (8 + row) * 8);
                const int grow = wrow + 2 * row;
                const bool issel = grow == sel0 || grow == sel1;
                uint4 yq = make_uint4(0, 0, 0, 0);
                if (pass && issel) yq = lds_v4(sb + SM_YV + (grow == sel0 ? 0 : 160) + ch * 16);
                const uint32_t m2 = dup_hi(st.x);
                const uint32_t* xu = &xv.x; const uint32_t* su = &sv.x; const uint32_t* yu = &yq.x;
                uint32_t o[4];
#pragma unroll
                for (int e = 0; e < 4; e++) {
                    const uint32_t d = hsub2(xu[e], m2);
                    const uint32_t bo = hadd2(pack_bf16(bf_lo(d) * st.y, bf_hi(d) * st.y), yu[e]);
                    const float ga = bf_lo(bo), gb = bf_hi(bo);
                    o[e] = hadd2(xu[e], hmul2(su[e], pack_bf16(silu_f(ga), silu_f(gb))));
                }
                if (issel == (pass != 0)) *reinterpret_cast<uint4*>(out + grow * DM + g * 80 + ch * 8) = make_uint4(o[0], o[1], o[2], o[3]);
            }
        }
        if (threadIdx.x == 0) { TL(6); st_relaxed_u32(&sc->epoch[cta * 32], epoch + 1); TL_DUMP(0);
 }
    }
}

typedef CUresult (*EncodeFn)(CUtensorMap*, CUtensorMapDataType, cuuint32_t, void*, const cuuint64_t*, const cuuint64_t*, const cuuint32_t*,
                             const cuuint32_t*, CUtensorMapInterleave, CUtensorMapSwizzle, CUtensorMapL2promotion, CUtensorMapFloatOOBfill);

static void encode3(EncodeFn enc, CUtensorMap* tm, const void* ptr, uint64_t d0, uint64_t d1, uint64_t d2, uint64_t s1, uint64_t s2,
                    uint32_t b0, uint32_t b1, uint32_t b2, CUtensorMapSwizzle swz, CUtensorMapL2promotion promo = CU_TENSOR_MAP_L2_PROMOTION_L2_128B) {
    cuuint64_t dims[3] = {d0, d1, d2}, strides[2] = {s1, s2};
    cuuint32_t box[3] = {b0, b1, b2}, es[3] = {1, 1, 1};
    enc(tm, CU_TENSOR_MAP_DATA_TYPE_BFLOAT16, 3, const_cast<void*>(ptr), dims, strides, box, es, CU_TENSOR_MAP_INTERLEAVE_NONE, swz,
        promo, CU_TENSOR_MAP_FLOAT_OOB_FILL_NONE);
}

}

extern "C" void kernel_launch(void* const* d_in, const int* in_sizes, int n_in, void* d_out, int out_size) {
    using namespace fk;
    (void)in_sizes; (void)n_in; (void)out_size;
    const __nv_bfloat16* x = (const __nv_bfloat16*)d_in[0];
    const __nv_bfloat16* wqkv = (const __nv_bfloat16*)d_in[1];
    const __nv_bfloat16* wo = (const __nv_bfloat16*)d_in[2];
    const __nv_bfloat16* wr = (const __nv_bfloat16*)d_in[4];
    const __nv_bfloat16* wg = (const __nv_bfloat16*)d_in[5];
    const __nv_bfloat16* wu = (const __nv_bfloat16*)d_in[6];
    const __nv_bfloat16* wd = (const __nv_bfloat16*)d_in[7];
    static EncodeFn enc = nullptr;
    static Scratch* scratch = nullptr;
    if (!enc) {
        void* fn = nullptr; cudaDriverEntryPointQueryResult qr;
        cudaGetDriverEntryPoint("cuTensorMapEncodeTiled", &fn, cudaEnableDefault, &qr);
        enc = (EncodeFn)fn;
        cudaFuncSetAttribute(fused_kernel, cudaFuncAttributeMaxDynamicSharedMemorySize, SM_TOTAL);
        cudaGetSymbolAddress((void**)&scratch, g_scratch);
    }
    CUtensorMap tx, tw, twt, two, twot, txs, tcs, tg, tu;
    encode3(enc, &tx, x, 640, 1024, 2, 2560, 1280, 64, 64, 2, CU_TENSOR_MAP_SWIZZLE_128B);
    encode3(enc, &tw, wqkv, 640, 640, 3, 3840, 1280, 64, 32, 3, CU_TENSOR_MAP_SWIZZLE_128B);
    encode3(enc, &twt, wqkv, 640, 640, 3, 3840, 1280, 16, 32, 3, CU_TENSOR_MAP_SWIZZLE_32B);
    encode3(enc, &two, wo, 640, 640, 1, 1280, 1280 * 640, 64, 64, 1, CU_TENSOR_MAP_SWIZZLE_128B);
    encode3(enc, &twot, wo, 640, 640, 1, 1280, 1280 * 640, 16, 128, 1, CU_TENSOR_MAP_SWIZZLE_32B);
    encode3(enc, &txs, x, 640, 1024, 2, 2560, 1280, 80, 64, 2, CU_TENSOR_MAP_SWIZZLE_NONE);
    encode3(enc, &tcs, wqkv, 64, 640, 30, 3840, 128, 64, 32, 8, CU_TENSOR_MAP_SWIZZLE_NONE);
    encode3(enc, &tg, wg, 1728, 640, 1, 3456, 3456 * 640, 32, 128, 1, CU_TENSOR_MAP_SWIZZLE_NONE);
    encode3(enc, &tu, wu, 1728, 640, 1, 3456, 3456 * 640, 32, 128, 1, CU_TENSOR_MAP_SWIZZLE_NONE);
    fused_kernel<<<NCTA + NHELP, NTHREADS, SM_TOTAL>>>(scratch, x, wqkv, wo, wr, wg, wu, wd, (__nv_bfloat16*)d_out, tx, tw, twt, two, twot, txs, tcs, tg, tu);
}
```

```cpp
#include <cuda_runtime.h>
#include <cuda_bf16.h>
#include <cuda.h>
#include <stdint.h>

#define DEVI __device__ __forceinline__

namespace fk {

constexpr int DM = 640;
constexpr int NCTA = 128, NIDLE = 4, NTHREADS = 384;
constexpr int NAUX = 96;
constexpr int NMOE = 54;
constexpr int STAGE = 47104;
constexpr int OFF_B = 16384, B_HALF = 15360;
constexpr int SM_WO = 0;
constexpr int SM_G7 = 81920;
constexpr int SM_WT = 87040;
constexpr int SM_DW = 107520;
constexpr int SM_OUT = 136192;
constexpr int SM_EX = 3 * STAGE;
constexpr int SM_O0 = 3 * STAGE + OFF_B, SM_O1 = 4 * STAGE, SM_O2 = SM_DW;
constexpr int SM_MW = 4 * STAGE;
constexpr int SM_PART = SM_MW + 28672;
constexpr int SM_BX = SM_MW + 35840;
constexpr int SM_XSEL = SM_BX + 2240;
constexpr int SM_ST = SM_XSEL + 2592;
constexpr int SM_GT = SM_ST + 1152;
constexpr int SM_GU = SM_GT + 320;
constexpr int SM_H = SM_GU + 256;
constexpr int SM_TOP = SM_H + 128;
constexpr int SM_BAR = SM_TOP + 16;
constexpr int SM_TL = SM_BAR + 256;
constexpr int SM_TOTAL = SM_TL;
static_assert(SM_TOTAL <= 232448 && SM_BAR % 8 == 0 && SM_XSEL % 16 == 0 && SM_ST % 16 == 0 && SM_GT % 16 == 0 && SM_BX % 1024 == 0 && SM_TOP % 16 == 0, "smem layout");
constexpr int BAR_FULL = 0, BAR_EMPTY = 4, BAR_F0B = 8, BAR_Y = 9, BAR_GW = 10, BAR_DW = 11, BAR_PX = 12, BAR_RS = 13,
              BAR_OF = 14  , BAR_OE = 19  , BAR_WO = 23, BAR_CS = 24, BAR_AE = 25  , BAR_PA = 30, NBAR = 31;
constexpr int JS = 5;
#define SIDE_KT 3
#define POLL_NS 100
#define PF1_NS 200
#define STAG 3
#define GP0 5
constexpr uint32_t EMPTY_WORD = 0xffffffffu;
struct Roles { unsigned short pair[NCTA / 2 + NIDLE / 2]; };
constexpr unsigned SPIN_MAX = 1u << 20;

struct Scratch {
    uint4 o[16][5][8][256];
    uint4 halo[NCTA][320];
    unsigned flag[16][8][8];
    float4 acc_cs[8][3][32];
    float4 acc_y[2][8][32][2];
    uint4 rec[2 * NCTA + 2];
    uint2 rowinfo[16][2][64];
    unsigned epoch[(NCTA + NIDLE) * 32];
};
__device__ Scratch g_scratch;
#define TL(i) do { } while (0)

DEVI uint32_t smem_u32(const void* p) { return (uint32_t)__cvta_generic_to_shared(p); }
DEVI void mbar_init(uint32_t bar, uint32_t cnt) { asm volatile("mbarrier.init.shared::cta.b64 [%0], %1;" :: "r"(bar), "r"(cnt)); }
DEVI void mbar_expect_tx(uint32_t bar, uint32_t bytes) { asm volatile("mbarrier.arrive.expect_tx.shared::cta.b64 _, [%0], %1;" :: "r"(bar), "r"(bytes) : "memory"); }
DEVI void mbar_arrive(uint32_t bar) { asm volatile("mbarrier.arrive.shared::cta.b64 _, [%0];" :: "r"(bar) : "memory"); }
DEVI uint32_t clk32() { uint32_t t; asm volatile("mov.u32 %0, %%clock;" : "=r"(t) :: "memory"); return t; }
DEVI bool mbar_try(uint32_t bar, uint32_t parity) {
    uint32_t ok;
    asm volatile("{\n.reg .pred p;\nmbarrier.try_wait.parity.shared::cta.b64 p, [%1], %2, 0x989680;\nselp.u32 %0, 1, 0, p;\n}" : "=r"(ok) : "r"(bar), "r"(parity) : "memory");
    return ok != 0;
}
DEVI void mbar_wait(uint32_t bar, uint32_t parity) {
    while (!mbar_try(bar, parity)) { }
}
DEVI bool elect_one() {
    uint32_t p;
    asm volatile("{\n.reg .pred P;\nelect.sync _|P, 0xffffffff;\nselp.u32 %0, 1, 0, P;\n}" : "=r"(p));
    return p != 0;
}
DEVI void tma3d(uint32_t dst, const CUtensorMap* tm, uint32_t bar, int c0, int c1, int c2) {
    asm volatile("cp.async.bulk.tensor.3d.shared::cluster.global.mbarrier::complete_tx::bytes [%0], [%1, {%3, %4, %5}], [%2];"
                 :: "r"(dst), "l"(tm), "r"(bar), "r"(c0), "r"(c1), "r"(c2) : "memory");
}
DEVI void tma3d_mc(uint32_t dst, const CUtensorMap* tm, uint32_t bar, int c0, int c1, int c2) {
    asm volatile("cp.async.bulk.tensor.3d.shared::cluster.global.mbarrier::complete_tx::bytes.multicast::cluster [%0], [%1, {%3, %4, %5}], [%2], %6;"
                 :: "r"(dst), "l"(tm), "r"(bar), "r"(c0), "r"(c1), "r"(c2), "h"((uint16_t)3) : "memory");
}
DEVI void tma2d(uint32_t dst, const CUtensorMap* tm, uint32_t bar, int c0, int c1) {
    asm volatile("cp.async.bulk.tensor.2d.shared::cluster.global.mbarrier::complete_tx::bytes [%0], [%1, {%3, %4}], [%2];"
                 :: "r"(dst), "l"(tm), "r"(bar), "r"(c0), "r"(c1) : "memory");
}
DEVI void tma2d_mc(uint32_t dst, const CUtensorMap* tm, uint32_t bar, int c0, int c1) {
    asm volatile("cp.async.bulk.tensor.2d.shared::cluster.global.mbarrier::complete_tx::bytes.multicast::cluster [%0], [%1, {%3, %4}], [%2], %5;"
                 :: "r"(dst), "l"(tm), "r"(bar), "r"(c0), "r"(c1), "h"((uint16_t)3) : "memory");
}
DEVI void mbar_arrive_both(uint32_t bar) {
    asm volatile("{\n.reg .b32 ra;\nmapa.shared::cluster.u32 ra, %0, 0;\nmbarrier.arrive.shared::cluster.b64 _, [ra];\n"
                 "mapa.shared::cluster.u32 ra, %0, 1;\nmbarrier.arrive.shared::cluster.b64 _, [ra];\n}" :: "r"(bar) : "memory");
}
DEVI void st_async_peer(uint32_t addr, uint32_t bar, uint32_t peer, uint32_t v) {
    asm volatile("{\n.reg .b32 ra, rb;\nmapa.shared::cluster.u32 ra, %0, %2;\nmapa.shared::cluster.u32 rb, %1, %2;\n"
                 "st.async.weak.shared::cluster.mbarrier::complete_tx::bytes.b32 [ra], %3, [rb];\n}" :: "r"(addr), "r"(bar), "r"(peer), "r"(v) : "memory");
}
DEVI void bulk_load(uint32_t dst, const void* src, uint32_t bytes, uint32_t bar) {
    asm volatile("cp.async.bulk.shared::cluster.global.mbarrier::complete_tx::bytes [%0], [%1], %2, [%3];" :: "r"(dst), "l"(src), "r"(bytes), "r"(bar) : "memory");
}
DEVI void cluster_arrive() { asm volatile("barrier.cluster.arrive.relaxed.aligned;" ::: "memory"); }
DEVI void cluster_wait() { asm volatile("barrier.cluster.wait.aligned;" ::: "memory"); }
DEVI void wg_fence() { asm volatile("wgmma.fence.sync.aligned;" ::: "memory"); }
DEVI void wg_commit() { asm volatile("wgmma.commit_group.sync.aligned;" ::: "memory"); }
template <int N> DEVI void wg_wait() { asm volatile("wgmma.wait_group.sync.aligned %0;" :: "n"(N) : "memory"); }
template <int ID, int N> DEVI void bar_sync() { asm volatile("bar.sync %0, %1;" :: "n"(ID), "n"(N) : "memory"); }
DEVI void spin_guard(unsigned& n) { if (++n > SPIN_MAX) __trap(); }
DEVI uint4 ld_relaxed_v4(const void* p) {
    uint4 v;
    asm volatile("ld.relaxed.gpu.global.v4.u32 {%0,%1,%2,%3}, [%4];" : "=r"(v.x), "=r"(v.y), "=r"(v.z), "=r"(v.w) : "l"(p) : "memory");
    return v;
}
DEVI void st_relaxed_v4(void* p, const uint4& v) {
    asm volatile("st.relaxed.gpu.global.v4.u32 [%0], {%1,%2,%3,%4};" :: "l"(p), "r"(v.x), "r"(v.y), "r"(v.z), "r"(v.w) : "memory");
}
DEVI unsigned ld_relaxed_u32(const void* p) { unsigned v; asm volatile("ld.relaxed.gpu.global.u32 %0, [%1];" : "=r"(v) : "l"(p) : "memory"); return v; }
DEVI unsigned ld_acquire_u32(const void* p) { unsigned v; asm volatile("ld.acquire.gpu.global.u32 %0, [%1];" : "=r"(v) : "l"(p) : "memory"); return v; }
DEVI void st_relaxed_u32(void* p, unsigned v) { asm volatile("st.relaxed.gpu.global.u32 [%0], %1;" :: "l"(p), "r"(v) : "memory"); }
DEVI void st_relaxed_v2(void* p, unsigned a, unsigned b) { asm volatile("st.relaxed.gpu.global.v2.u32 [%0], {%1,%2};" :: "l"(p), "r"(a), "r"(b) : "memory"); }
DEVI uint4 ld_gen_v4(const void* p) {
    uint4 v;
    asm volatile("ld.relaxed.gpu.v4.u32 {%0,%1,%2,%3}, [%4];" : "=r"(v.x), "=r"(v.y), "=r"(v.z), "=r"(v.w) : "l"(p) : "memory");
    return v;
}
DEVI void st_gen_v4(void* p, const uint4& v) { asm volatile("st.relaxed.gpu.v4.u32 [%0], {%1,%2,%3,%4};" :: "l"(p), "r"(v.x), "r"(v.y), "r"(v.z), "r"(v.w) : "memory"); }
DEVI float sqrt_approx(float x) { float y; asm("sqrt.approx.ftz.f32 %0, %1;" : "=f"(y) : "f"(x)); return y; }
DEVI void red_add_u32(unsigned* p, unsigned v) { asm volatile("red.relaxed.gpu.global.add.u32 [%0], %1;" :: "l"(p), "r"(v) : "memory"); }
DEVI void red_add_v4(void* p, float a, float b, float c, float d) {
    asm volatile("red.relaxed.gpu.global.add.v4.f32 [%0], {%1,%2,%3,%4};" :: "l"(p), "f"(a), "f"(b), "f"(c), "f"(d) : "memory");
}
DEVI float4 ld_relaxed_f4(const void* p) {
    float4 v;
    asm volatile("ld.relaxed.gpu.global.v4.f32 {%0,%1,%2,%3}, [%4];" : "=f"(v.x), "=f"(v.y), "=f"(v.z), "=f"(v.w) : "l"(p) : "memory");
    return v;
}
DEVI void tma3d_store(const CUtensorMap* tm, uint32_t src, int c0, int c1, int c2) {
    asm volatile("cp.async.bulk.tensor.3d.global.shared::cta.bulk_group [%0, {%2, %3, %4}], [%1];\ncp.async.bulk.commit_group;\ncp.async.bulk.wait_group.read 0;"
                 :: "l"(tm), "r"(src), "r"(c0), "r"(c1), "r"(c2) : "memory");
}
DEVI uint32_t lds_u16(uint32_t a) { unsigned short v; asm volatile("ld.shared.u16 %0, [%1];" : "=h"(v) : "r"(a)); return v; }
DEVI void fence_gpu() { asm volatile("fence.acq_rel.gpu;" ::: "memory"); }
DEVI uint4 ldg_v4(const void* p) {
    uint4 v;
    asm volatile("ld.global.L1::no_allocate.v4.u32 {%0,%1,%2,%3}, [%4];" : "=r"(v.x), "=r"(v.y), "=r"(v.z), "=r"(v.w) : "l"(p) : "memory");
    return v;
}
DEVI uint4 lds_v4(uint32_t a) { uint4 v; asm volatile("ld.shared.v4.u32 {%0,%1,%2,%3}, [%4];" : "=r"(v.x), "=r"(v.y), "=r"(v.z), "=r"(v.w) : "r"(a)); return v; }
DEVI void sts_v4(uint32_t a, const uint4& v) { asm volatile("st.shared.v4.u32 [%0], {%1,%2,%3,%4};" :: "r"(a), "r"(v.x), "r"(v.y), "r"(v.z), "r"(v.w) : "memory"); }
DEVI void sts_f4(uint32_t a, float x, float y, float z, float w) { asm volatile("st.shared.v4.f32 [%0], {%1,%2,%3,%4};" :: "r"(a), "f"(x), "f"(y), "f"(z), "f"(w) : "memory"); }
DEVI float2 lds_f2(uint32_t a) { float2 v; asm volatile("ld.shared.v2.f32 {%0,%1}, [%2];" : "=f"(v.x), "=f"(v.y) : "r"(a)); return v; }
DEVI float4 lds_f4(uint32_t a) { float4 v; asm volatile("ld.shared.v4.f32 {%0,%1,%2,%3}, [%4];" : "=f"(v.x), "=f"(v.y), "=f"(v.z), "=f"(v.w) : "r"(a)); return v; }
DEVI void ldsm4(uint32_t addr, uint32_t& a, uint32_t& b, uint32_t& c, uint32_t& d) {
    asm volatile("ldmatrix.sync.aligned.m8n8.x4.shared.b16 {%0,%1,%2,%3}, [%4];" : "=r"(a), "=r"(b), "=r"(c), "=r"(d) : "r"(addr));
}
DEVI void ldsm4_if(bool on, uint32_t addr, uint32_t (&v)[4]) {
    asm volatile("{\n.reg .pred p;\nsetp.ne.b32 p, %5, 0;\n@p ldmatrix.sync.aligned.m8n8.x4.shared.b16 {%0,%1,%2,%3}, [%4];\n}"
                 : "+r"(v[0]), "+r"(v[1]), "+r"(v[2]), "+r"(v[3]) : "r"(addr), "r"((uint32_t)on));
}
DEVI void ldsm4t(uint32_t addr, uint32_t (&v)[4]) {
    asm volatile("ldmatrix.sync.aligned.m8n8.x4.trans.shared.b16 {%0,%1,%2,%3}, [%4];" : "=r"(v[0]), "=r"(v[1]), "=r"(v[2]), "=r"(v[3]) : "r"(addr));
}
DEVI void ldsm2(uint32_t addr, uint32_t& a, uint32_t& b) { asm volatile("ldmatrix.sync.aligned.m8n8.x2.shared.b16 {%0,%1}, [%2];" : "=r"(a), "=r"(b) : "r"(addr)); }
DEVI void cp_async16(uint32_t dst, const void* src) { asm volatile("cp.async.cg.shared.global [%0], [%1], 16;" :: "r"(dst), "l"(src) : "memory"); }
DEVI void prefetch_l2_bulk(const void* p, uint32_t bytes) { asm volatile("cp.async.bulk.prefetch.L2.global [%0], %1;" :: "l"(p), "r"(bytes) : "memory"); }
DEVI void sts_u16(uint32_t a, uint32_t v) { asm volatile("st.shared.u16 [%0], %1;" :: "r"(a), "h"((unsigned short)v) : "memory"); }
DEVI uint32_t hfma2(uint32_t a, uint32_t b, uint32_t c) { uint32_t d; asm("fma.rn.bf16x2 %0, %1, %2, %3;" : "=r"(d) : "r"(a), "r"(b), "r"(c)); return d; }
DEVI float tanh_f(float x) { float t; asm("tanh.approx.f32 %0, %1;" : "=f"(t) : "f"(x)); return t; }
DEVI void stsm4(uint32_t addr, uint32_t a, uint32_t b, uint32_t c, uint32_t d) {
    asm volatile("stmatrix.sync.aligned.m8n8.x4.shared.b16 [%0], {%1,%2,%3,%4};" :: "r"(addr), "r"(a), "r"(b), "r"(c), "r"(d) : "memory");
}
DEVI uint32_t movm(uint32_t a) { uint32_t d; asm("movmatrix.sync.aligned.m8n8.trans.b16 %0, %1;" : "=r"(d) : "r"(a)); return d; }
DEVI void mma16(float (&c)[4], uint32_t a0, uint32_t a1, uint32_t a2, uint32_t a3, uint32_t b0, uint32_t b1) {
    asm("mma.sync.aligned.m16n8k16.row.col.f32.bf16.bf16.f32 {%0,%1,%2,%3}, {%4,%5,%6,%7}, {%8,%9}, {%0,%1,%2,%3};"
                 : "+f"(c[0]), "+f"(c[1]), "+f"(c[2]), "+f"(c[3]) : "r"(a0), "r"(a1), "r"(a2), "r"(a3), "r"(b0), "r"(b1));
}
DEVI void mma8(float (&c)[4], uint32_t a0, uint32_t a1, uint32_t b0) {
    asm("mma.sync.aligned.m16n8k8.row.col.f32.bf16.bf16.f32 {%0,%1,%2,%3}, {%4,%5}, {%6}, {%0,%1,%2,%3};"
                 : "+f"(c[0]), "+f"(c[1]), "+f"(c[2]), "+f"(c[3]) : "r"(a0), "r"(a1), "r"(b0));
}
DEVI uint32_t pack_bf16(float lo, float hi) { uint32_t d; asm("cvt.rn.bf16x2.f32 %0, %1, %2;" : "=r"(d) : "f"(hi), "f"(lo)); return d; }
DEVI float bf_lo(uint32_t v) { return __uint_as_float(v << 16); }
DEVI float bf_hi(uint32_t v) { return __uint_as_float(v & 0xffff0000u); }
DEVI float bfr(float x) { return __bfloat162float(__float2bfloat16_rn(x)); }
DEVI float ex2(float x) { float y; asm("ex2.approx.ftz.f32 %0, %1;" : "=f"(y) : "f"(x)); return y; }
DEVI float rcp(float x) { float y; asm("rcp.approx.ftz.f32 %0, %1;" : "=f"(y) : "f"(x)); return y; }
DEVI float sigmoid_f(float x) { return rcp(1.0f + ex2(x * -1.4426950408889634f)); }
DEVI float silu_f(float x) { const float h = 0.5f * x; float t; asm("tanh.approx.f32 %0, %1;" : "=f"(t) : "f"(h)); return fmaf(h, t, h); }
DEVI uint32_t hsub2(uint32_t a, uint32_t b) { uint32_t d; asm("sub.rn.bf16x2 %0, %1, %2;" : "=r"(d) : "r"(a), "r"(b)); return d; }
DEVI uint32_t hadd2(uint32_t a, uint32_t b) { uint32_t d; asm("add.rn.bf16x2 %0, %1, %2;" : "=r"(d) : "r"(a), "r"(b)); return d; }
DEVI uint32_t hmul2(uint32_t a, uint32_t b) { uint32_t d; asm("mul.rn.bf16x2 %0, %1, %2;" : "=r"(d) : "r"(a), "r"(b)); return d; }
DEVI uint32_t dup_hi(float x) { return __byte_perm(__float_as_uint(x), 0, 0x3232); }
DEVI void sts_u32(uint32_t a, uint32_t v) { asm volatile("st.shared.u32 [%0], %1;" :: "r"(a), "r"(v) : "memory"); }
DEVI void sts_f2(uint32_t a, float x, float y) { asm volatile("st.shared.v2.f32 [%0], {%1,%2};" :: "r"(a), "f"(x), "f"(y) : "memory"); }
DEVI uint2 lds_v2(uint32_t a) { uint2 v; asm volatile("ld.shared.v2.u32 {%0,%1}, [%2];" : "=r"(v.x), "=r"(v.y) : "r"(a)); return v; }
DEVI uint32_t lds_u32(uint32_t a) { uint32_t v; asm volatile("ld.shared.u32 %0, [%1];" : "=r"(v) : "r"(a)); return v; }
DEVI float lds_f32(uint32_t a) { float v; asm volatile("ld.shared.f32 %0, [%1];" : "=f"(v) : "r"(a)); return v; }
DEVI float shfl_x(float v, int o) { return __shfl_xor_sync(0xffffffffu, v, o); }

DEVI void wgmma_rs_n192(float (&d)[120], uint32_t a0, uint32_t a1, uint32_t a2, uint32_t a3, uint32_t blo, uint32_t scale_d) {
    asm volatile("{\n.reg .b64 db;\n.reg .pred p;\n"
        "setp.ne.b32 p, %101, 0;\n"
        "mov.b64 db, {%100, 0x40000040};\n"
        "wgmma.mma_async.sync.aligned.m64n192k16.f32.bf16.bf16 "
        "{%0, %1, %2, %3, %4, %5, %6, %7, %8, %9, %10, %11, %12, %13, %14, %15, %16, %17, %18, %19, %20, %21, %22, %23, %24, %25, %26, %27, %28, %29, %30, %31, %32, %33, %34, %35, %36, %37, %38, %39, %40, %41, %42, %43, %44, %45, %46, %47, %48, %49, %50, %51, %52, %53, %54, %55, %56, %57, %58, %59, %60, %61, %62, %63, %64, %65, %66, %67, %68, %69, %70, %71, %72, %73, %74, %75, %76, %77, %78, %79, %80, %81, %82, %83, %84, %85, %86, %87, %88, %89, %90, %91, %92, %93, %94, %95}, "
        "{%96, %97, %98, %99}, db, p, 1, 1, 1;\n}\n"
        : "+f"(d[0]), "+f"(d[1]), "+f"(d[2]), "+f"(d[3]), "+f"(d[4]), "+f"(d[5]), "+f"(d[6]), "+f"(d[7]), "+f"(d[8]), "+f"(d[9]), "+f"(d[10]), "+f"(d[11]), "+f"(d[12]), "+f"(d[13]), "+f"(d[14]), "+f"(d[15]), "+f"(d[16]), "+f"(d[17]), "+f"(d[18]), "+f"(d[19]), "+f"(d[20]), "+f"(d[21]), "+f"(d[22]), "+f"(d[23]), "+f"(d[24]), "+f"(d[25]), "+f"(d[26]), "+f"(d[27]), "+f"(d[28]), "+f"(d[29]), "+f"(d[30]), "+f"(d[31]), "+f"(d[32]), "+f"(d[33]), "+f"(d[34]), "+f"(d[35]), "+f"(d[36]), "+f"(d[37]), "+f"(d[38]), "+f"(d[39]), "+f"(d[40]), "+f"(d[41]), "+f"(d[42]), "+f"(d[43]), "+f"(d[44]), "+f"(d[45]), "+f"(d[46]), "+f"(d[47]), "+f"(d[48]), "+f"(d[49]), "+f"(d[50]), "+f"(d[51]), "+f"(d[52]), "+f"(d[53]), "+f"(d[54]), "+f"(d[55]), "+f"(d[56]), "+f"(d[57]), "+f"(d[58]), "+f"(d[59]), "+f"(d[60]), "+f"(d[61]), "+f"(d[62]), "+f"(d[63]), "+f"(d[64]), "+f"(d[65]), "+f"(d[66]), "+f"(d[67]), "+f"(d[68]), "+f"(d[69]), "+f"(d[70]), "+f"(d[71]), "+f"(d[72]), "+f"(d[73]), "+f"(d[74]), "+f"(d[75]), "+f"(d[76]), "+f"(d[77]), "+f"(d[78]), "+f"(d[79]), "+f"(d[80]), "+f"(d[81]), "+f"(d[82]), "+f"(d[83]), "+f"(d[84]), "+f"(d[85]), "+f"(d[86]), "+f"(d[87]), "+f"(d[88]), "+f"(d[89]), "+f"(d[90]), "+f"(d[91]), "+f"(d[92]), "+f"(d[93]), "+f"(d[94]), "+f"(d[95])
        : "r"(a0), "r"(a1), "r"(a2), "r"(a3), "r"(blo), "r"(scale_d));
}
DEVI void wgmma_rs_n48(float (&d)[120], uint32_t a0, uint32_t a1, uint32_t a2, uint32_t a3, uint32_t blo, uint32_t scale_d) {
    asm volatile("{\n.reg .b64 db;\n.reg .pred p;\n"
        "setp.ne.b32 p, %29, 0;\n"
        "mov.b64 db, {%28, 0xc0000010};\n"
        "wgmma.mma_async.sync.aligned.m64n48k16.f32.bf16.bf16 "
        "{%0, %1, %2, %3, %4, %5, %6, %7, %8, %9, %10, %11, %12, %13, %14, %15, %16, %17, %18, %19, %20, %21, %22, %23}, "
        "{%24, %25, %26, %27}, db, p, 1, 1, 1;\n}\n"
        : "+f"(d[96]), "+f"(d[97]), "+f"(d[98]), "+f"(d[99]), "+f"(d[100]), "+f"(d[101]), "+f"(d[102]), "+f"(d[103]), "+f"(d[104]), "+f"(d[105]), "+f"(d[106]), "+f"(d[107]), "+f"(d[108]), "+f"(d[109]), "+f"(d[110]), "+f"(d[111]), "+f"(d[112]), "+f"(d[113]), "+f"(d[114]), "+f"(d[115]), "+f"(d[116]), "+f"(d[117]), "+f"(d[118]), "+f"(d[119])
        : "r"(a0), "r"(a1), "r"(a2), "r"(a3), "r"(blo), "r"(scale_d));
}
DEVI void wgmma_rs_n192x(float (&d)[120], uint32_t a0, uint32_t a1, uint32_t a2, uint32_t a3, uint32_t blo) {
    asm volatile("{\n.reg .b64 db;\n.reg .pred p;\n"
        "mov.b64 db, {%100, 0x40000000};\n"
        "wgmma.mma_async.sync.aligned.m64n192k16.f32.bf16.bf16 "
        "{%0, %1, %2, %3, %4, %5, %6, %7, %8, %9, %10, %11, %12, %13, %14, %15, %16, %17, %18, %19, %20, %21, %22, %23, %24, %25, %26, %27, %28, %29, %30, %31, %32, %33, %34, %35, %36, %37, %38, %39, %40, %41, %42, %43, %44, %45, %46, %47, %48, %49, %50, %51, %52, %53, %54, %55, %56, %57, %58, %59, %60, %61, %62, %63, %64, %65, %66, %67, %68, %69, %70, %71, %72, %73, %74, %75, %76, %77, %78, %79, %80, %81, %82, %83, %84, %85, %86, %87, %88, %89, %90, %91, %92, %93, %94, %95}, "
        "{%96, %97, %98, %99}, db, 1, 1, 1, 1;\n}\n"
        : "+f"(d[0]), "+f"(d[1]), "+f"(d[2]), "+f"(d[3]), "+f"(d[4]), "+f"(d[5]), "+f"(d[6]), "+f"(d[7]), "+f"(d[8]), "+f"(d[9]), "+f"(d[10]), "+f"(d[11]), "+f"(d[12]), "+f"(d[13]), "+f"(d[14]), "+f"(d[15]), "+f"(d[16]), "+f"(d[17]), "+f"(d[18]), "+f"(d[19]), "+f"(d[20]), "+f"(d[21]), "+f"(d[22]), "+f"(d[23]), "+f"(d[24]), "+f"(d[25]), "+f"(d[26]), "+f"(d[27]), "+f"(d[28]), "+f"(d[29]), "+f"(d[30]), "+f"(d[31]), "+f"(d[32]), "+f"(d[33]), "+f"(d[34]), "+f"(d[35]), "+f"(d[36]), "+f"(d[37]), "+f"(d[38]), "+f"(d[39]), "+f"(d[40]), "+f"(d[41]), "+f"(d[42]), "+f"(d[43]), "+f"(d[44]), "+f"(d[45]), "+f"(d[46]), "+f"(d[47]), "+f"(d[48]), "+f"(d[49]), "+f"(d[50]), "+f"(d[51]), "+f"(d[52]), "+f"(d[53]), "+f"(d[54]), "+f"(d[55]), "+f"(d[56]), "+f"(d[57]), "+f"(d[58]), "+f"(d[59]), "+f"(d[60]), "+f"(d[61]), "+f"(d[62]), "+f"(d[63]), "+f"(d[64]), "+f"(d[65]), "+f"(d[66]), "+f"(d[67]), "+f"(d[68]), "+f"(d[69]), "+f"(d[70]), "+f"(d[71]), "+f"(d[72]), "+f"(d[73]), "+f"(d[74]), "+f"(d[75]), "+f"(d[76]), "+f"(d[77]), "+f"(d[78]), "+f"(d[79]), "+f"(d[80]), "+f"(d[81]), "+f"(d[82]), "+f"(d[83]), "+f"(d[84]), "+f"(d[85]), "+f"(d[86]), "+f"(d[87]), "+f"(d[88]), "+f"(d[89]), "+f"(d[90]), "+f"(d[91]), "+f"(d[92]), "+f"(d[93]), "+f"(d[94]), "+f"(d[95])
        : "r"(a0), "r"(a1), "r"(a2), "r"(a3), "r"(blo));
}
DEVI void wgmma_rs_n48x(float (&d)[120], uint32_t a0, uint32_t a1, uint32_t a2, uint32_t a3, uint32_t blo) {
    asm volatile("{\n.reg .b64 db;\n.reg .pred p;\n"
        "mov.b64 db, {%28, 0xc0000000};\n"
        "wgmma.mma_async.sync.aligned.m64n48k16.f32.bf16.bf16 "
        "{%0, %1, %2, %3, %4, %5, %6, %7, %8, %9, %10, %11, %12, %13, %14, %15, %16, %17, %18, %19, %20, %21, %22, %23}, "
        "{%24, %25, %26, %27}, db, 1, 1, 1, 1;\n}\n"
        : "+f"(d[96]), "+f"(d[97]), "+f"(d[98]), "+f"(d[99]), "+f"(d[100]), "+f"(d[101]), "+f"(d[102]), "+f"(d[103]), "+f"(d[104]), "+f"(d[105]), "+f"(d[106]), "+f"(d[107]), "+f"(d[108]), "+f"(d[109]), "+f"(d[110]), "+f"(d[111]), "+f"(d[112]), "+f"(d[113]), "+f"(d[114]), "+f"(d[115]), "+f"(d[116]), "+f"(d[117]), "+f"(d[118]), "+f"(d[119])
        : "r"(a0), "r"(a1), "r"(a2), "r"(a3), "r"(blo));
}
DEVI void wgmma_rs_n80(float (&d)[40], uint32_t a0, uint32_t a1, uint32_t a2, uint32_t a3, uint32_t blo, uint32_t scale_d) {
    asm volatile("{\n.reg .b64 db;\n.reg .pred p;\n"
        "setp.ne.b32 p, %45, 0;\n"
        "mov.b64 db, {%44, 0x40000040};\n"
        "wgmma.mma_async.sync.aligned.m64n80k16.f32.bf16.bf16 "
        "{%0, %1, %2, %3, %4, %5, %6, %7, %8, %9, %10, %11, %12, %13, %14, %15, %16, %17, %18, %19, %20, %21, %22, %23, %24, %25, %26, %27, %28, %29, %30, %31, %32, %33, %34, %35, %36, %37, %38, %39}, "
        "{%40, %41, %42, %43}, db, p, 1, 1, 1;\n}\n"
        : "+f"(d[0]), "+f"(d[1]), "+f"(d[2]), "+f"(d[3]), "+f"(d[4]), "+f"(d[5]), "+f"(d[6]), "+f"(d[7]), "+f"(d[8]), "+f"(d[9]), "+f"(d[10]), "+f"(d[11]), "+f"(d[12]), "+f"(d[13]), "+f"(d[14]), "+f"(d[15]), "+f"(d[16]), "+f"(d[17]), "+f"(d[18]), "+f"(d[19]), "+f"(d[20]), "+f"(d[21]), "+f"(d[22]), "+f"(d[23]), "+f"(d[24]), "+f"(d[25]), "+f"(d[26]), "+f"(d[27]), "+f"(d[28]), "+f"(d[29]), "+f"(d[30]), "+f"(d[31]), "+f"(d[32]), "+f"(d[33]), "+f"(d[34]), "+f"(d[35]), "+f"(d[36]), "+f"(d[37]), "+f"(d[38]), "+f"(d[39])
        : "r"(a0), "r"(a1), "r"(a2), "r"(a3), "r"(blo), "r"(scale_d));
}
DEVI void wgmma_ss_n80(float (&d)[40], uint32_t alo, uint32_t blo) {
    asm volatile("{\n.reg .b64 da, db;\n"
        "mov.b64 da, {%40, 0x10};\n"
        "mov.b64 db, {%41, 0x40000040};\n"
        "wgmma.mma_async.sync.aligned.m64n80k16.f32.bf16.bf16 "
        "{%0, %1, %2, %3, %4, %5, %6, %7, %8, %9, %10, %11, %12, %13, %14, %15, %16, %17, %18, %19, %20, %21, %22, %23, %24, %25, %26, %27, %28, %29, %30, %31, %32, %33, %34, %35, %36, %37, %38, %39}, "
        "da, db, 1, 1, 1, 0, 1;\n}\n"
        : "+f"(d[0]), "+f"(d[1]), "+f"(d[2]), "+f"(d[3]), "+f"(d[4]), "+f"(d[5]), "+f"(d[6]), "+f"(d[7]), "+f"(d[8]), "+f"(d[9]), "+f"(d[10]), "+f"(d[11]), "+f"(d[12]), "+f"(d[13]), "+f"(d[14]), "+f"(d[15]), "+f"(d[16]), "+f"(d[17]), "+f"(d[18]), "+f"(d[19]), "+f"(d[20]), "+f"(d[21]), "+f"(d[22]), "+f"(d[23]), "+f"(d[24]), "+f"(d[25]), "+f"(d[26]), "+f"(d[27]), "+f"(d[28]), "+f"(d[29]), "+f"(d[30]), "+f"(d[31]), "+f"(d[32]), "+f"(d[33]), "+f"(d[34]), "+f"(d[35]), "+f"(d[36]), "+f"(d[37]), "+f"(d[38]), "+f"(d[39])
        : "r"(alo), "r"(blo));
}

DEVI unsigned redux_max(unsigned v) { return __reduce_max_sync(0xffffffffu, v); }

DEVI void wait_records(const Scratch* sc, int lane, unsigned tag, uint4 (&q)[8]) {
    unsigned spins = 0;
    while (true) {
        unsigned bad = 0;
#pragma unroll
        for (int j = 0; j < 8; j++) q[j] = ld_relaxed_v4(&sc->rec[lane + 32 * j]);
        __syncwarp();
#pragma unroll
        for (int j = 0; j < 8; j++) bad |= q[j].x ^ tag;
        if (__all_sync(0xffffffffu, (bad & 31) == 0)) break;
        __nanosleep(POLL_NS);
        spin_guard(spins);
    }
}

template <int ODD, int HALF> DEVI void pack_kv(const float (&acc)[120], uint32_t (&K)[10][2], uint32_t (&V)[10][2]) {
#pragma unroll
    for (int b = 0; b < 10; b++) {
        const int pb = ODD ? (b + 8) % 10 : b, jk = pb < 8 ? 8 + pb : 18 + pb, jv = pb < 8 ? 16 + pb : 20 + pb;
        V[b][HALF] = movm(pack_bf16(acc[4 * jv + 2 * HALF], acc[4 * jv + 2 * HALF + 1]));
        K[b][HALF] = pack_bf16(acc[4 * jk + 2 * HALF], acc[4 * jk + 2 * HALF + 1]);
    }
}
template <int ODD> DEVI void pack_q(const float (&acc)[120], uint32_t (&Q)[10][2]) {
#pragma unroll
    for (int b = 0; b < 10; b++) {
        const int pb = ODD ? (b + 8) % 10 : b, jq = pb < 8 ? pb : 16 + pb;
        Q[b][0] = pack_bf16(acc[4 * jq], acc[4 * jq + 1]); Q[b][1] = pack_bf16(acc[4 * jq + 2], acc[4 * jq + 3]);
    }
}

#define SRC(i) ((i) == 0 ? g : ((i) - 1 < g ? (i) - 1 : (i)))

__global__ void __cluster_dims__(2, 1, 1) __launch_bounds__(NTHREADS, 1) fused_kernel(
    Scratch* __restrict__ sc,
    const __nv_bfloat16* __restrict__ x, const __nv_bfloat16* __restrict__ wqkv, const __nv_bfloat16* __restrict__ wo, const __nv_bfloat16* __restrict__ wr,
    const __nv_bfloat16* __restrict__ wd, __nv_bfloat16* __restrict__ out, const int by_sm, const __grid_constant__ Roles roles,
    const __grid_constant__ CUtensorMap tm_x, const __grid_constant__ CUtensorMap tm_w, const __grid_constant__ CUtensorMap tm_wt,
    const __grid_constant__ CUtensorMap tm_wo, const __grid_constant__ CUtensorMap tm_d,
    const __grid_constant__ CUtensorMap tm_g, const __grid_constant__ CUtensorMap tm_u, const __grid_constant__ CUtensorMap tm_o)
{
    extern __shared__ __align__(1024) unsigned char smem[];
    uint32_t sb, smid;
    asm volatile("mov.u32 %0, %1;" : "=r"(sb) : "r"(smem_u32(smem)));
    asm volatile("mov.u32 %0, %%smid;" : "=r"(smid));
    const uint32_t bid = blockIdx.x, tid = threadIdx.x;
    const unsigned cta = roles.pair[(by_sm ? smid : bid) >> 1] * 2 + (bid & 1);
    const int warp = __shfl_sync(0xffffffffu, tid >> 5, 0), lane = tid & 31;
    const uint32_t bars = sb + SM_BAR;
    if (warp == 8) {
        if (elect_one()) {
            mbar_init(bars + BAR_FULL * 8, 1); mbar_init(bars + BAR_F0B * 8, 1);
            asm volatile("fence.mbarrier_init.release.cluster;" ::: "memory");
        }
        __syncwarp();
    }
    if (warp == 9) {
        if (elect_one()) {
#pragma unroll
            for (int s = 1; s < NBAR; s++) if (s != BAR_F0B) mbar_init(bars + s * 8, (s >> 2) == 1 ? 4 : (s == BAR_PA ? 8 : (s >= BAR_AE ? 3 : (s >= BAR_OE + 2 ? 2 : 1))));
            asm volatile("fence.mbarrier_init.release.cluster;" ::: "memory");
        }
        __syncwarp();
    }
    cluster_arrive();
#define NPF 2
    if (warp < NPF) {
        const unsigned i = bid * 31 + min(lane, 30);
        const char* q = i < 2048 ? reinterpret_cast<const char*>(x) + i * 1280 + warp * 128
                                 : (i < 3968 ? reinterpret_cast<const char*>(wqkv) + (i - 2048 + warp * 1920) * 128 : reinterpret_cast<const char*>(wr) + (i - 3968) * 128);
        if (warp) __nanosleep(PF1_NS * warp);
        if (i < 3978) asm volatile("prefetch.global.L2 [%0];" :: "l"(q) : "memory");
    }
    if (cta >= NCTA) {
        const unsigned tag = ld_relaxed_u32(&sc->epoch[cta * 32]) + 1;
        if (cta == NCTA) {
#pragma unroll 1
            for (int i = tid; i < 1792; i += NTHREADS) st_relaxed_v4(&sc->acc_cs[0][0][0] + i, make_uint4(0, 0, 0, 0));
            __syncthreads();
            if (tid < 2) { fence_gpu(); st_relaxed_v4(&sc->rec[2 * NCTA + lane], make_uint4(tag, 0, 0, 0)); }
        }
        cluster_wait();
        if (warp == 0) {
            uint4 q[8];
            __nanosleep(4000);
            wait_records(sc, lane, tag, q);
            if (lane == 0) st_relaxed_u32(&sc->epoch[cta * 32], tag);
        }
        return;
    }
    const int rank = cta & 1, g = (cta >> 1) & 7, G = cta >> 4, m = 2 * G + rank, odd = g & 1;
    const int cm = g * 80 + odd * 16, ct = g * 80 + 64 - odd * 64;

    if (warp == 8 && elect_one()) {
        const uint32_t st = sb + 2 * STAGE;
        mbar_expect_tx(bars + BAR_FULL * 8, OFF_B + B_HALF); mbar_expect_tx(bars + BAR_F0B * 8, B_HALF + 1280);
        tma3d(st, &tm_x, bars + BAR_FULL * 8, 0, m * 64, 0);
        tma3d(st + OFF_B, &tm_w, bars + BAR_FULL * 8, cm, 0, 0);
        tma3d(st + OFF_B + 12288, &tm_wt, bars + BAR_FULL * 8, ct, 0, 0);
        tma3d(st + OFF_B + B_HALF, &tm_w, bars + BAR_F0B * 8, cm, 32, 0);
        tma3d(st + OFF_B + B_HALF + 12288, &tm_wt, bars + BAR_F0B * 8, ct, 32, 0);
        bulk_load(sb + SM_XSEL, wr, 1280, bars + BAR_F0B * 8);
        TL(16);
    }
    __syncwarp();
    if (warp >= 8) {
        asm volatile("setmaxnreg.dec.sync.aligned.u32 104;");
        const int mi = g < 6 ? G * 6 + g : 46 + G;
        const bool moe = g < 6 || (g == 6 && G >= 2);
        const CUtensorMap* tm_gu = rank ? &tm_u : &tm_g;
        if (warp == 8) {
            cluster_wait();
#pragma unroll 1
            for (int kt = 1; kt < 10; kt++) {
                if (kt >= 4) { mbar_wait(bars + (BAR_AE + min(kt, 8) - 4) * 8, 0); mbar_wait(bars + (BAR_EMPTY + (kt & 3)) * 8, ((kt >> 2) - 1) & 1); }
                if (elect_one()) {
                    const uint32_t fb = bars + (BAR_FULL + (kt & 3)) * 8, st = sb + ((kt + 2) & 3) * STAGE;
                    mbar_expect_tx(fb, STAGE);
                    tma3d(st, &tm_x, fb, kt * 64, m * 64, 0);
                    tma3d_mc(st + OFF_B + rank * B_HALF, &tm_w, fb, cm, kt * 64 + rank * 32, 0);
                    tma3d(st + OFF_B + 12288, &tm_wt, fb, ct, kt * 64, 0);
                    tma3d(st + OFF_B + B_HALF + 12288, &tm_wt, fb, ct, kt * 64 + 32, 0);
                    if (moe && (unsigned)(kt - GP0) < 3u) tma2d(sb + SM_MW + (kt - GP0 + 4) * 5120, tm_gu, bars + BAR_GW * 8, mi * 32, (kt - GP0 + 4) * 80);
                    if (kt == 3) TL(17);
                }
                __syncwarp();
            }
            if (elect_one()) {
                mbar_expect_tx(bars + BAR_WO * 8, 81920);
                if (moe) prefetch_l2_bulk(wd + (mi * 32 + rank * 16) * DM, 20480);
            }
#pragma unroll 1
            for (int ph = 0; ph < 2; ph++) {
                mbar_wait(bars + (BAR_EMPTY + 2 + ph) * 8, 1);
                if (elect_one()) {
                    if (ph && moe) { mbar_expect_tx(bars + BAR_GW * 8, 40960); tma2d(sb + SM_G7, tm_gu, bars + BAR_GW * 8, mi * 32, 560); }
#pragma unroll 1
                    for (int i = ph * 4 + rank; i < ph * 4 + 4; i += 2) tma2d_mc(sb + SM_WO + i * 10240, &tm_wo, bars + BAR_WO * 8, cm, SRC(i) * 80);
                }
                __syncwarp();
            }
            mbar_wait(bars + BAR_EMPTY * 8, 0);
            if (moe && elect_one()) { mbar_expect_tx(bars + BAR_DW * 8, 20480); tma3d(sb + SM_DW, &tm_d, bars + BAR_DW * 8, 0, mi * 32, rank * 5); }
            __syncwarp();
            {
                const int r = lane >> 1;
#pragma unroll 1
                for (int i = 0; i < 8; i++) {
                    const __nv_bfloat16* src = wo + (SRC(i) * 80 + r) * DM + ct + (lane & 1) * 8;
                    const uint32_t dst = sb + SM_WT + (i & 1) * 10240 + r * 128 + ((((i & 6) + (lane & 1)) ^ (r & 7)) << 4);
#pragma unroll
                    for (int t = 0; t < 5; t++) cp_async16(dst + t * 2048, src + t * 16 * DM);
                }
                asm volatile("cp.async.wait_all;\nfence.proxy.async.shared::cta;" ::: "memory");
                __syncwarp();
                if (lane == 0) { mbar_arrive(bars + BAR_WO * 8); TL(19); }
            }
            const uint4* os = &sc->o[m][0][0][0];
            const uint4* fl = reinterpret_cast<const uint4*>(&sc->flag[m][0][0]) + (lane & 15);
            mbar_wait(bars + (BAR_EMPTY + 1) * 8, 0);
            mbar_wait(bars + BAR_PA * 8, 0);
            unsigned lvl = 0, spins = 0;
#pragma unroll 1
            for (int t = 0; t < 5; t++) {
                while (lvl <= t) {
                    const uint4 f = ld_relaxed_v4(fl);
                    lvl = __reduce_min_sync(0xffffffffu, min(min(f.x, f.y), min(f.z, f.w)));
                    spin_guard(spins);
                }
                if (t) mbar_wait(bars + (BAR_OE + t - 1) * 8, 0);
                if (elect_one()) {
                    const uint32_t dst = sb + (t == 2 ? SM_O2 : ((t == 0 || t == 3) ? SM_O0 : SM_O1)), fb = bars + (BAR_OF + t) * 8;
                    mbar_expect_tx(fb, 28672);
                    if (g > 0) bulk_load(dst, os + t * 2048, g * 4096, fb);
                    if (g < 7) bulk_load(dst + g * 4096, os + t * 2048 + (g + 1) * 256, (7 - g) * 4096, fb);
                    TL(48 + t);
                }
                __syncwarp();
            }
        } else {
            const int ta = tid - 288, wa = warp - 9, c = lane & 3, r = lane >> 2;
            const unsigned tag = ld_relaxed_u32(&sc->epoch[cta * 32]) + 1;
            uint2* const rid = &sc->rowinfo[m][wa & 1][8 * g + r];
            if (wa < 2) {
                if (c == 0) st_relaxed_v2(rid, 0, tag - 1);
                if (ta < 2) st_relaxed_v4(&sc->rec[2 * cta + ta], make_uint4(tag - 1, 0, 0, 0));
            }
            const int l = min(lane, 29), part = l < 24 ? l >> 3 : (l - 24) >> 1;
            uint32_t ad[4];
#pragma unroll
            for (int i = 0; i < 4; i++) {
                const int row = 4 * G + i, ch = c + 4 * ((r ^ i) & 1);
                ad[i] = wa == 2 ? OFF_B + rank * B_HALF + (l < 24 ? part * 4096 + row * 128 + (((l ^ row) & 7) << 4) : 12288 + part * 1024 + row * 32 + (((l ^ G) & 1) << 4))
                                : (i < 2 ? wa * 8192 + (8 * g + r) * 128 + ((ch ^ r) << 4) : SM_XSEL + ch * 16);
                ad[i] = __shfl_sync(0xffffffffu, sb + ad[i], lane);
            }
            const uint32_t side = sb + SM_MW + wa * 5120 + lane * 16;
            uint4 *ro = &sc->o[m][0][g][ta], *rh = &sc->halo[m * 8 + g][ta];
            asm volatile("" : "+l"(ro), "+l"(rh));
            if (ta < 70) { sts_v4(sb + SM_BX + ta * 32, make_uint4(0, 0, 0, 0)); sts_v4(sb + SM_BX + ta * 32 + 16, make_uint4(0, 0, 0, 0)); }
            float s[8];
#pragma unroll
            for (int e = 0; e < 8; e++) s[e] = 0.f;
            cluster_wait();
            mbar_wait(bars + BAR_F0B * 8, 0);
#pragma unroll 1
            for (int kt = 0; kt < 10; kt++) {
                uint32_t so = ((kt + 2) & 3) * STAGE;
                if (kt < JS) mbar_wait(bars + (BAR_FULL + (kt & 3)) * 8, kt >> 2);
                else {
                    if (kt == JS) {
                        asm volatile("cp.async.wait_all;" ::: "memory");
                        ad[0] = side; ad[1] = side + 512;
                        if (wa == 2) { ad[2] = side + 1024; ad[3] = side + 1536; }
                    }
                    so = (kt - JS) << (wa == 2 ? 11 : 10);
                }
                const uint32_t so2 = wa == 2 ? so : kt * 128;
                uint4 v[4];
#pragma unroll
                for (int i = 0; i < 4; i++) v[i] = lds_v4(ad[i] + (i < 2 ? so : so2));
                if (kt < 5) {
                    const uint4 e = make_uint4(EMPTY_WORD, EMPTY_WORD, EMPTY_WORD, EMPTY_WORD);
                    st_relaxed_v4(ro, e); st_relaxed_v4(ro + 96, e);
                    if (wa < 2) { st_relaxed_v4(ro + 192, e); st_relaxed_v4(rh, e); }
                    ro += 2048; rh += 64;
                }
                if (kt == SIDE_KT) {
                    const char* p0 = wa == 2 ? reinterpret_cast<const char*>(wqkv + (64 * JS + 20 * m) * 1920 + part * DM + (l < 24 ? cm + (l & 7) * 8 : ct + (l & 1) * 8))
                                             : reinterpret_cast<const char*>(x + (m * 128 + g * 16 + 2 * r + wa) * DM + 64 * JS + (c + 4 * (r & 1)) * 8);
                    const int d1 = wa == 2 ? 3840 : 64 - 128 * (r & 1), d2 = wa == 2 ? 7680 : 128;
#pragma unroll 1
                    for (int j = 0; j < (wa == 2 ? 10 : 5); j++, p0 += d2) { cp_async16(side + j * 1024, p0); cp_async16(side + j * 1024 + 512, p0 + d1); }
                    if (ta < 2) st_relaxed_v4(&sc->flag[m][g][ta * 4], make_uint4(0, 0, 0, 0));
                }
                if (wa == 2) {
#pragma unroll
                    for (int i = 0; i < 4; i++) {
#pragma unroll
                        for (int e = 0; e < 4; e++) { s[2 * e] += bf_lo((&v[i].x)[e]); s[2 * e + 1] += bf_hi((&v[i].x)[e]); }
                    }
                } else {
#pragma unroll
                    for (int i = 0; i < 2; i++) {
#pragma unroll
                        for (int e = 0; e < 4; e++) {
                            const float a = bf_lo((&v[i].x)[e]), b = bf_hi((&v[i].x)[e]), wl = bf_lo((&v[2 + i].x)[e]), wh = bf_hi((&v[2 + i].x)[e]);
                            s[0] += a; s[1] = fmaf(a, a, s[1]); s[2] = fmaf(a, wl, s[2]); s[3] += wl;
                            s[4] += b; s[5] = fmaf(b, b, s[5]); s[6] = fmaf(b, wh, s[6]); s[7] += wh;
                        }
                    }
                }
                __syncwarp();
                if (kt < JS && lane == 0) mbar_arrive(bars + (BAR_AE + kt) * 8);
            }
            if (wa == 2) {
                float4* const acs = &sc->acc_cs[g][0][lane];
                unsigned spins = 0;
                while (ld_relaxed_u32(&sc->rec[2 * NCTA]) != tag) spin_guard(spins);
                red_add_v4(acs, s[0], s[1], s[2], 1.f); red_add_v4(acs + 32, s[3], s[4], s[5], 1.f); red_add_v4(acs + 64, s[6], s[7], 0.f, 1.f);
                if (lane == 0) { mbar_expect_tx(bars + BAR_PX * 8, 256); TL(18); }
                bar_sync<3, NAUX>();
                if (moe && elect_one()) {
#pragma unroll 1
                    for (int gp = 0; gp < 4; gp++) tma2d(sb + SM_MW + gp * 5120, tm_gu, bars + BAR_GW * 8, mi * 32, gp * 80);
                }
                __syncwarp();
                fence_gpu();
                asm volatile("bar.arrive 6, 96;" ::: "memory");
                if (lane == 0) TL(20);
                float4 a, b, d;
                while (true) {
                    a = ld_relaxed_f4(acs); b = ld_relaxed_f4(acs + 32); d = ld_relaxed_f4(acs + 64);
                    if (__all_sync(0xffffffffu, a.w + b.w + d.w == 48.f)) break;
                    __nanosleep(POLL_NS);
                    spin_guard(spins);
                }
                s[0] = a.x; s[1] = a.y; s[2] = a.z; s[3] = b.x; s[4] = b.y; s[5] = b.z; s[6] = d.x; s[7] = d.y;
#pragma unroll 1
                for (int row = 3 * part; row < 3 * part + 3; row++) {
                    uint32_t o[4];
#pragma unroll
                    for (int e = 0; e < 4; e++) { o[e] = pack_bf16(s[2 * e], s[2 * e + 1]); s[2 * e] -= bf_lo(o[e]); s[2 * e + 1] -= bf_hi(o[e]); }
                    if (lane < 30) sts_v4(sb + SM_BX + (l < 24 ? row * 128 + (((l ^ row) & 7) << 4) : 1792 + row * 32 + (((l ^ (row >> 2)) & 1) << 4)), make_uint4(o[0], o[1], o[2], o[3]));
                }
                asm volatile("fence.proxy.async.shared::cta;" ::: "memory");
                __syncwarp();
                if (lane == 0) { mbar_arrive(bars + BAR_CS * 8); TL(25); }
            } else {
                asm volatile("fence.proxy.async.shared::cta;\nbar.arrive 3, 96;" ::: "memory");
#pragma unroll
                for (int e = 0; e < 4; e++) { s[e] += s[4 + e]; s[e] += shfl_x(s[e], 1); }
#pragma unroll
                for (int e = 0; e < 4; e++) s[e] += shfl_x(s[e], 2);
                const float mean = s[0] * (1.0f / DM), mb = bfr(mean);
                const float sd = bfr(sqrt_approx(bfr(bfr(fmaxf(fmaf(-mean, mean, s[1] * (1.0f / DM)), 0.f)) + 1e-5f)));
                const uint32_t info = (__float_as_uint(mb) >> 16) | (__float_as_uint(sd) & 0xffff0000u);
                if (c == 0) st_relaxed_v2(rid, info, tag);
                if (ta == 0) TL(22);
                const uint32_t u = __float_as_uint(bfr(fmaf(-mb, s[3], s[2]) * rcp(sd))) >> 16;
                const unsigned key = (((u & 0x8000u) ? (u ^ 0xffffu) : (u | 0x8000u)) << 16) | ((2047 - (m * 128 + g * 16 + 2 * r + wa)) << 5) | (tag & 31);
                const unsigned k1 = redux_max(key), k2 = redux_max(key == k1 ? 0u : key);
                const unsigned i1 = redux_max(key == k1 ? info : 0u), i2 = redux_max(key == k2 ? info : 0u);
                {
                    const uint4* r0 = reinterpret_cast<const uint4*>(&sc->rowinfo[m][wa][0]);
                    uint4 a, b; unsigned spins = 0;
                    while (true) {
                        a = ld_relaxed_v4(r0 + lane); b = ld_relaxed_v4(r0 + (m > 0 ? 28 - 64 : 0) + c);
                        if (__all_sync(0xffffffffu, ((a.y ^ tag) | (a.w ^ tag) | (b.y ^ tag) | (b.w ^ tag)) == 0)) break;
                        __nanosleep(POLL_NS);
                        spin_guard(spins);
                    }
                    sts_f4(sb + SM_ST + (wa * 72 + 8 + 2 * lane) * 8, bf_lo(a.x), rcp(bf_hi(a.x)), bf_lo(a.z), rcp(bf_hi(a.z)));
                    if (lane < 4) sts_f4(sb + SM_ST + (wa * 72 + 2 * lane) * 8, bf_lo(b.x), rcp(bf_hi(b.x)), bf_lo(b.z), rcp(bf_hi(b.z)));
                }
                bar_sync<6, NAUX>();
                if (lane == 0) { st_relaxed_v4(&sc->rec[2 * cta + wa], make_uint4(k1, k2, i1, i2)); if (wa == 0) { mbar_arrive(bars + BAR_CS * 8); TL(24); } }
            }
            if (wa == 1) {
                uint4 q[8];
                wait_records(sc, lane, tag, q);
                unsigned a = 0, b = 0;
#pragma unroll
                for (int j = 0; j < 8; j++) { b = max(max(b, q[j].y), min(a, q[j].x)); a = max(a, q[j].x); }
                const unsigned k1 = redux_max(a), k2 = redux_max(a == k1 ? b : a);
                const int sel0 = 2047 - ((k1 >> 5) & 2047), sel1 = 2047 - ((k2 >> 5) & 2047);
                uint4 xq[5];
                const int tk = lane >> 4;
#pragma unroll
                for (int j = 0; j < 5; j++) xq[j] = ldg_v4(reinterpret_cast<const uint4*>(x + (tk ? sel1 : sel0) * DM) + (lane & 15) + 16 * j);
                if (lane == 0) { sts_v4(sb + SM_TOP, make_uint4(sel0, sel1, k1, k2)); mbar_arrive(bars + BAR_RS * 8); TL(23); }
                unsigned i1 = 0, i2 = 0;
#pragma unroll
                for (int j = 0; j < 8; j++) { if (q[j].x == k1) i1 = q[j].z; if (q[j].x == k2) i2 = q[j].z; if (q[j].y == k2) i2 = q[j].w; }
                i1 = redux_max(i1); i2 = redux_max(i2);
                const uint32_t info = tk ? i2 : i1, mm = __byte_perm(info, 0, 0x1010);
                const float rs = 1.0f / bf_hi(info), rh = bfr(rs);
                const uint32_t rh2 = dup_hi(rh), rl2 = pack_bf16(rs - rh, rs - rh);
#pragma unroll
                for (int j = 0; j < 5; j++) {
                    uint32_t o[4];
#pragma unroll
                    for (int e = 0; e < 4; e++) { const uint32_t d = hsub2((&xq[j].x)[e], mm); o[e] = hfma2(d, rh2, hmul2(d, rl2)); }
                    sts_v4(sb + SM_XSEL + tk * 1296 + (lane & 15) * 16 + j * 256, make_uint4(o[0], o[1], o[2], o[3]));
                }
            }
            bar_sync<3, NAUX>();
            if (moe) {
                const int krow = (lane >> 4) * 8 + (lane & 7), ch = (lane >> 3) & 1;
                const uint32_t wofs = krow * 64 + ((ch ^ (krow >> 1)) & 3) * 16, xa = sb + SM_XSEL + (lane & 1) * 1296 + ch * 16;
                float d[4][4];
#pragma unroll
                for (int e = 0; e < 16; e++) d[e >> 2][e & 3] = 0.f;
                mbar_wait(bars + BAR_GW * 8, 0);
                mbar_wait(bars + (BAR_EMPTY + 1) * 8, 0);
                if (ta == 0) TL(26);
#pragma unroll 1
                for (int ks = wa; ks < 40; ks += 6) {
                    uint32_t a[4][4], b[2][2];
#pragma unroll
                    for (int h = 0; h < 2; h++) {
                        const int k2 = min(ks + 3 * h, 39);
                        const uint32_t wp = sb + (k2 < 35 ? SM_MW : SM_G7 - 35 * 1024) + k2 * 1024 + wofs;
                        ldsm4t(wp, a[2 * h]); ldsm4t(wp ^ 32, a[2 * h + 1]); ldsm2(xa + k2 * 32, b[h][0], b[h][1]);
                    }
                    if (ks + 3 > 39) b[1][0] = b[1][1] = 0;
#pragma unroll
                    for (int e = 0; e < 4; e++) mma16(d[e], a[e][0], a[e][1], a[e][2], a[e][3], b[e >> 1][0], b[e >> 1][1]);
                }
                bar_sync<3, NAUX>();
                if (ta == 0) { mbar_arrive(bars + BAR_OE * 8); TL(27); }
                if (c == 0) {
#pragma unroll
                    for (int e = 0; e < 4; e++) sts_f2(sb + SM_PART + wa * 256 + (e * 8 + r) * 8, d[e >> 1][2 * (e & 1)] + d[2 + (e >> 1)][2 * (e & 1)], d[e >> 1][2 * (e & 1) + 1] + d[2 + (e >> 1)][2 * (e & 1) + 1]);
                }
                bar_sync<3, NAUX>();
                if (wa < 2) {
                    const float sum = bfr(lds_f32(sb + SM_PART + ta * 4) + lds_f32(sb + SM_PART + 256 + ta * 4) + lds_f32(sb + SM_PART + 512 + ta * 4));
                    st_async_peer(sb + SM_GU + ta * 4, bars + BAR_PX * 8, rank ^ 1, __float_as_uint(sum));
                    mbar_wait(bars + BAR_PX * 8, 0);
                    const float oth = lds_f32(sb + SM_GU + ta * 4), gs = rank ? oth : sum, us = rank ? sum : oth;
                    sts_u16(sb + SM_H + (ta & 1) * 64 + (ta >> 1) * 2, pack_bf16(bfr(gs * sigmoid_f(gs)) * us, 0.f));
                }
                mbar_wait(bars + BAR_DW * 8, 0);
                bar_sync<3, NAUX>();
                uint32_t hb[4];
                ldsm4(sb + SM_H + (lane & 1) * 64 + (lane >> 3) * 16, hb[0], hb[1], hb[2], hb[3]);
                float yv[2][5];
#pragma unroll
                for (int e = 0; e < 5; e++) yv[1][e] = 0.f;
#pragma unroll 1
                for (int gg = wa; gg < 4; gg += 3) {
#pragma unroll
                    for (int b = 0; b < 5; b++) {
                        const int nb = gg * 5 + b;
                        const uint32_t wp = sb + SM_DW + (nb >> 2) * 4096 + krow * 128 + ((((nb & 3) * 2 + ch) ^ (krow & 7)) << 4);
                        uint32_t a0[4], a1[4];
                        ldsm4t(wp, a0); ldsm4t(wp + 2048, a1);
                        float o[4] = {0.f, 0.f, 0.f, 0.f};
                        mma16(o, a0[0], a0[1], a0[2], a0[3], hb[0], hb[1]); mma16(o, a1[0], a1[1], a1[2], a1[3], hb[2], hb[3]);
                        yv[0][b] = yv[1][b];
                        yv[1][b] = (c & 2) ? ((c & 1) ? o[3] : o[2]) : ((c & 1) ? o[1] : o[0]);
                    }
                }
                bar_sync<3, NAUX>();
                if (ta == 0) { mbar_arrive(bars + (BAR_OE + 1) * 8); TL(28); }
                mbar_wait(bars + BAR_OF * 8, 0);
                float4* ya = &sc->acc_y[mi & 1][rank * 4 + (wa ? wa : 3)][lane][0];
                red_add_v4(ya, yv[1][0], yv[1][1], yv[1][2], 1.f); red_add_v4(ya + 1, yv[1][3], yv[1][4], 0.f, 1.f);
                if (wa == 0) { red_add_v4(ya - 192, yv[0][0], yv[0][1], yv[0][2], 1.f); red_add_v4(ya - 191, yv[0][3], yv[0][4], 0.f, 1.f); }
                if (ta == 0) TL(29);
            } else if (ta == 0) { mbar_arrive(bars + BAR_OE * 8); mbar_arrive(bars + (BAR_OE + 1) * 8); }
            if (wa == 1) {
                const uint4 rec = lds_v4(sb + SM_TOP);
                if ((rec.x >> 7) == m || (rec.y >> 7) == m) {
                    const uint32_t ks = ((c & 1) ? rec.w : rec.z) >> 16;
                    const float sg = bfr(sigmoid_f(__uint_as_float(((ks & 0x8000u) ? (ks & 0x7fffu) : (ks ^ 0xffffu)) << 16)));
                    const float4* ya = &sc->acc_y[0][g][lane][0];
                    float4 a, b, a2, b2; unsigned spins = 0;
                    while (true) {
                        a = ld_relaxed_f4(ya); b = ld_relaxed_f4(ya + 1); a2 = ld_relaxed_f4(ya + 512); b2 = ld_relaxed_f4(ya + 513);
                        if (__all_sync(0xffffffffu, a.w + b.w + a2.w + b2.w == 2.f * NMOE)) break;
                        __nanosleep(POLL_NS);
                        spin_guard(spins);
                    }
                    const float yy[5] = {a.x + a2.x, a.y + a2.y, a.z + a2.z, b.x + b2.x, b.y + b2.y};
                    const int col = r + 8 * (c >> 1);
#pragma unroll
                    for (int e = 0; e < 5; e++)
                        sts_u16(sb + SM_GT + (c & 1) * 160 + (col + 16 * e) * 2,
                                pack_bf16(silu_f(bfr(bf_lo(lds_u16(sb + SM_XSEL + (c & 1) * 1296 + (g * 80 + col + 16 * e) * 2)) + bfr(bfr(yy[e]) * sg))), 0.f));
                    __syncwarp();
                    if (lane == 0) TL(30);
                }
                if (lane == 0) { mbar_arrive(bars + BAR_Y * 8); st_relaxed_u32(&sc->epoch[cta * 32], tag); }
            }
        }
    } else {
        asm volatile("setmaxnreg.inc.sync.aligned.u32 200;");
        const int p = warp >> 2, w = warp & 3, c = lane & 3, r = lane >> 2;
        const uint32_t stb = sb + SM_ST + (p * 72 + w * 16) * 8;
        float acc[120];
#pragma unroll
        for (int i = 0; i < 120; i++) asm volatile("" : "=f"(acc[i]));
        uint32_t xs[5][4];
#pragma unroll
        for (int i = 0; i < 20; i++) asm volatile("" : "=r"(xs[i >> 2][i & 3]));
        cluster_wait();
        {
            const int lr = w * 16 + (lane & 15);
            uint32_t st = __shfl_sync(0xffffffffu, sb + 2 * STAGE + p * 8192 + lr * 128 + (((lr & 7) ^ (lane >> 4)) << 4), lane);
            const bool lead = __shfl_sync(0xffffffffu, tid & 127, lane) == 0;
            uint32_t blo = (((sb + 2 * STAGE + OFF_B) & 0x3ffffu) >> 4) | ((4096u >> 4) << 16);
            const uint32_t tdiff = (12288u >> 4) + ((1024u >> 4) << 16) - ((4096u >> 4) << 16);
            const int kx = (5 * g) >> 2;
            uint32_t af[4][4];
            mbar_wait(bars + BAR_FULL * 8, 0);
            if (tid == 0) TL(32);
            ldsm4(st, af[0][0], af[0][1], af[0][2], af[0][3]);
#pragma unroll 1
            for (int kt = 0; kt < 10; kt++) {
#pragma unroll
                for (int j = 0; j < 4; j++) {
                    uint32_t (&nx)[4] = af[(j + 1) & 3];
                    if (j == 2 && kt == 0) mbar_wait(bars + BAR_F0B * 8, 0);
                    if (j == 3 && kt < 9) {
                        st += (kt & 3) == 1 ? -3 * STAGE : STAGE;
                        mbar_wait(bars + (BAR_FULL + ((kt + 1) & 3)) * 8, ((kt + 1) >> 2) & 1);
                    }
                    ldsm4(st ^ (((j + 1) & 3) << 5), nx[0], nx[1], nx[2], nx[3]);
                    wg_fence();
                    const uint32_t sd = j ? 1u : (uint32_t)kt;
                    wgmma_rs_n48(acc, af[j][0], af[j][1], af[j][2], af[j][3], blo + tdiff + (j >> 1) * (B_HALF >> 4) + (j & 1) * 32, sd);
                    wgmma_rs_n192(acc, af[j][0], af[j][1], af[j][2], af[j][3], blo + (j >> 1) * (B_HALF >> 4) + (j & 1) * 128, sd);
                    wg_commit();
                    wg_wait<1>();
                    if (j == 0 && kt > 0 && lead) mbar_arrive_both(bars + (BAR_EMPTY + ((kt - 1) & 3)) * 8);
                    if (j == 1 && (unsigned)(kt - kx) < 2u) {
#pragma unroll
                        for (int t = 0; t < 5; t++) {
                            const int ks = 5 * g + (t < 4 ? t + odd : 4 - 4 * odd);
                            ldsm4_if((ks >> 2) == kt, st ^ ((ks & 3) << 5), xs[t]);
                        }
                    }
                }
                blo += (kt & 3) == 1 ? -3 * (STAGE >> 4) : (STAGE >> 4);
            }
        }
        mbar_wait(bars + BAR_CS * 8, 0);
        if (tid == 0) TL(10);
        const float2 st0 = lds_f2(stb + (8 + r) * 8), st1 = lds_f2(stb + (16 + r) * 8);
        {
            const uint32_t msk = c == 0 ? 0xffffffffu : (c == 1 ? 0x0000ffffu : 0u);
            const uint32_t e0 = dup_hi(-st0.x) & msk, e1 = dup_hi(-st1.x) & msk;
            wg_fence();
            wgmma_rs_n48x(acc, e0, e1, 0u, 0u, (((sb + SM_BX + 1792) & 0x3ffffu) >> 4) | ((96u >> 4) << 16));
            wgmma_rs_n192x(acc, e0, e1, 0u, 0u, (((sb + SM_BX) & 0x3ffffu) >> 4) | ((384u >> 4) << 16));
            wg_commit();
        }
        const float rs0 = st0.y, rs1 = st1.y;
        const uint4 sP = lds_v4(stb + (2 * c) * 8), sB = lds_v4(stb + (8 + 2 * c) * 8), sC = lds_v4(stb + (16 + 2 * c) * 8);
        const bool up0 = 2 * c > r, up1 = 2 * c + 1 > r;
        const float k00 = __uint_as_float(up0 ? sP.y : sB.y), k01 = __uint_as_float(up1 ? sP.w : sB.w);
        const float k10 = __uint_as_float(up0 ? sB.y : sC.y), k11 = __uint_as_float(up1 ? sB.w : sC.w);
        const float sc2 = 0.22360679774997896f * 1.4426950408889634f;
        const float f00 = rs0 * k00 * sc2, f01 = rs0 * k01 * sc2, f10 = rs1 * k10 * sc2, f11 = rs1 * k11 * sc2;
        const bool first = (m == 0 && w == 0);
        const float b00 = (first && up0) ? -1e30f : 0.f, b01 = (first && up1) ? -1e30f : 0.f;
        const uint32_t mup = (up0 ? 0x0000ffffu : 0u) | (up1 ? 0xffff0000u : 0u);
        uint4* const exs = reinterpret_cast<uint4*>(smem + SM_EX) + p * 512 + lane;
        uint4* hdst = w == 3 ? &sc->halo[m * 8 + g][p * 160 + lane] : exs + w * 160;
        const uint4* hsrc = w > 0 ? exs + (w - 1) * 160 : (m > 0 ? &sc->halo[m * 8 + g - 8][p * 160 + lane] : exs);
        uint32_t* ob = reinterpret_cast<uint32_t*>(&sc->o[m][0][g][warp * 32]) + lane;
        unsigned* of_ = &sc->flag[m][g][warp];
        asm volatile("" : "+l"(hdst), "+l"(hsrc), "+l"(ob), "+l"(of_));
        mbar_wait(bars + BAR_RS * 8, 0);
        if (p == 0) bar_sync<1, 128>(); else bar_sync<2, 128>();
        wg_wait<0>();
        if ((tid & 127) == 0) { mbar_arrive_both(bars + (BAR_EMPTY + 1) * 8); TL(2 + p); }
        uint32_t Q[10][2], K[10][2], V[10][2], Kp[10], Vp[10];
        if (odd) pack_kv<1, 1>(acc, K, V); else pack_kv<0, 1>(acc, K, V);
        st_gen_v4(hdst, make_uint4(K[0][1], K[1][1], K[2][1], K[3][1])); st_gen_v4(hdst + 32, make_uint4(K[4][1], K[5][1], K[6][1], K[7][1]));
        st_gen_v4(hdst + 64, make_uint4(K[8][1], K[9][1], V[0][1], V[1][1])); st_gen_v4(hdst + 96, make_uint4(V[2][1], V[3][1], V[4][1], V[5][1]));
        st_gen_v4(hdst + 128, make_uint4(V[6][1], V[7][1], V[8][1], V[9][1]));
        if (tid == 96) TL(11);
        if (odd) { pack_kv<1, 0>(acc, K, V); pack_q<1>(acc, Q); } else { pack_kv<0, 0>(acc, K, V); pack_q<0>(acc, Q); }
        {
            if (p == 0) bar_sync<1, 128>(); else bar_sync<2, 128>();
            uint4 rcv[5];
            unsigned spins = 0;
            while (true) {
#pragma unroll
                for (int i = 0; i < 5; i++) rcv[i] = ld_gen_v4(hsrc + i * 32);
                const unsigned mx = max(max(max(rcv[0].x, rcv[1].x), max(rcv[2].x, rcv[3].x)), rcv[4].x);
                if (__all_sync(0xffffffffu, mx != EMPTY_WORD) || ++spins > SPIN_MAX) break;
            }
            Kp[0] = rcv[0].x; Kp[1] = rcv[0].y; Kp[2] = rcv[0].z; Kp[3] = rcv[0].w; Kp[4] = rcv[1].x; Kp[5] = rcv[1].y; Kp[6] = rcv[1].z; Kp[7] = rcv[1].w;
            Kp[8] = rcv[2].x; Kp[9] = rcv[2].y; Vp[0] = rcv[2].z; Vp[1] = rcv[2].w; Vp[2] = rcv[3].x; Vp[3] = rcv[3].y; Vp[4] = rcv[3].z; Vp[5] = rcv[3].w;
            Vp[6] = rcv[4].x; Vp[7] = rcv[4].y; Vp[8] = rcv[4].z; Vp[9] = rcv[4].w;
        }
        if (tid == 0) TL(4);
        if (tid == 32) TL(5);
        uint32_t of[10][2];
#define PUBLISH(t) do { st_relaxed_u32(ob + (t) * 8192, of[2 * (t)][0]); st_relaxed_u32(ob + (t) * 8192 + 32, of[2 * (t) + 1][0]); \
            st_relaxed_u32(ob + (t) * 8192 + 64, of[2 * (t)][1]); st_relaxed_u32(ob + (t) * 8192 + 96, of[2 * (t) + 1][1]); \
            if (lane == 0) st_relaxed_u32(of_, (t) + 1); } while (0)
#pragma unroll
        for (int hp = 0; hp < 2; hp++) {
            float sp[2][4], sm_[2][4], sn[2][4], O[5][4];
            const int bz = 5 * hp + 2;
#pragma unroll
            for (int b = 0; b < 5; b++) { O[b][0] = O[b][1] = O[b][2] = O[b][3] = 0.f; }
#pragma unroll
            for (int h = 0; h < 2; h++) {
                const int bx = 5 * hp + 3 * h, by = bx + 1;
                const bool qmine = h ? (c >= 2) : (c < 2);
                const uint32_t qz0 = qmine ? Q[bz][0] : 0u, qz1 = qmine ? Q[bz][1] : 0u;
#pragma unroll
                for (int e = 0; e < 4; e++) { sp[h][e] = 0.f; sm_[h][e] = 0.f; sn[h][e] = 0.f; }
                mma16(sm_[h], Q[bx][0], Q[bx][1], Q[by][0], Q[by][1], K[bx][0], K[by][0]);
                mma16(sn[h], Q[bx][0], Q[bx][1], Q[by][0], Q[by][1], K[bx][1], K[by][1]);
                mma16(sp[h], Q[bx][0], Q[bx][1], Q[by][0], Q[by][1], Kp[bx], Kp[by]);
                mma8(sm_[h], qz0, qz1, K[bz][0]); mma8(sn[h], qz0, qz1, K[bz][1]); mma8(sp[h], qz0, qz1, Kp[bz]);
            }
            float l[2][4], mx[2][2];
#pragma unroll
            for (int h = 0; h < 2; h++) {
                l[h][0] = fmaf(up0 ? sp[h][0] : sm_[h][0], f00, b00); l[h][1] = fmaf(up1 ? sp[h][1] : sm_[h][1], f01, b01);
                l[h][2] = (up0 ? sm_[h][2] : sn[h][2]) * f10; l[h][3] = (up1 ? sm_[h][3] : sn[h][3]) * f11;
                mx[h][0] = fmaxf(l[h][0], l[h][1]); mx[h][1] = fmaxf(l[h][2], l[h][3]);
            }
#pragma unroll
            for (int o = 1; o < 4; o <<= 1) {
#pragma unroll
                for (int h = 0; h < 2; h++) { mx[h][0] = fmaxf(mx[h][0], shfl_x(mx[h][0], o)); mx[h][1] = fmaxf(mx[h][1], shfl_x(mx[h][1], o)); }
            }
            float sum[2][2];
#pragma unroll
            for (int h = 0; h < 2; h++) {
                l[h][0] = ex2(l[h][0] - mx[h][0]); l[h][1] = ex2(l[h][1] - mx[h][0]); l[h][2] = ex2(l[h][2] - mx[h][1]); l[h][3] = ex2(l[h][3] - mx[h][1]);
                sum[h][0] = l[h][0] + l[h][1]; sum[h][1] = l[h][2] + l[h][3];
            }
#pragma unroll
            for (int o = 1; o < 4; o <<= 1) {
#pragma unroll
                for (int h = 0; h < 2; h++) { sum[h][0] += shfl_x(sum[h][0], o); sum[h][1] += shfl_x(sum[h][1], o); }
            }
#pragma unroll
            for (int h = 0; h < 2; h++) {
                const int bx = 5 * hp + 3 * h, by = bx + 1;
                const float i0 = rcp(sum[h][0]), i1 = rcp(sum[h][1]);
                const uint32_t pl = pack_bf16(l[h][0] * k00 * i0, l[h][1] * k01 * i0), ph = pack_bf16(l[h][2] * k10 * i1, l[h][3] * k11 * i1);
                const uint32_t a0 = pl & mup, a2 = pl & ~mup, a3 = ph & mup, c1 = ph & ~mup;
                const bool vmine = h ? (r >= 4) : (r < 4);
                mma16(O[3 * h], a0, 0u, a2, a3, Vp[bx], V[bx][0]);
                mma16(O[3 * h + 1], a0, 0u, a2, a3, Vp[by], V[by][0]);
                mma16(O[2], a0, 0u, a2, a3, vmine ? Vp[bz] : 0u, vmine ? V[bz][0] : 0u);
                mma8(O[3 * h], 0u, c1, V[bx][1]); mma8(O[3 * h + 1], 0u, c1, V[by][1]); mma8(O[2], 0u, c1, vmine ? V[bz][1] : 0u);
            }
#pragma unroll
            for (int b = 0; b < 5; b++) { of[5 * hp + b][0] = pack_bf16(O[b][0], O[b][1]); of[5 * hp + b][1] = pack_bf16(O[b][2], O[b][3]); }
            if (hp == 0) { PUBLISH(0); PUBLISH(1); if (lane == 0) mbar_arrive(bars + BAR_PA * 8); }
            if (tid == 0) TL(6 + hp);
            if (tid == 32) TL(8 + hp);
        }
#define TRK 0
        float acc2[40];
#pragma unroll
        for (int i = 0; i < 40; i++) asm volatile("" : "=f"(acc2[i]));
        uint32_t gate[5][4];
        PUBLISH(2);
        if (TRK == 0) { PUBLISH(3); PUBLISH(4); }
        const float rh0 = bfr(0.5f * rs0), rh1 = bfr(0.5f * rs1);
        const uint32_t gm[2] = {dup_hi(st0.x), dup_hi(st1.x)}, gh[2] = {dup_hi(rh0), dup_hi(rh1)};
        const uint32_t gl[2] = {pack_bf16(0.5f * rs0 - rh0, 0.5f * rs0 - rh0), pack_bf16(0.5f * rs1 - rh1, 0.5f * rs1 - rh1)};
        mbar_wait(bars + BAR_WO * 8, 0);
        bar_sync<4, 256>();
        if (tid == 0) TL(13);
        const uint32_t wlo = ((sb + SM_WO) & 0x3ffffu) >> 4, alo = (((sb + p * 2048) & 0x3ffffu) >> 4) | (8u << 16);
#define WDESC(ks) (wlo + (ks) * 128 + (((SM_WT - SM_WO + ((ks) % 10 - (ks)) * 2048 + ((ks) / 10) * 32) >> 4) << 16))
        wg_fence();
#pragma unroll
        for (int t = 0; t < 5; t++) wgmma_rs_n80(acc2, of[2 * t][0], of[2 * t][1], of[2 * t + 1][0], of[2 * t + 1][1], WDESC(t), t != 0);
        wg_commit();
#pragma unroll
        for (int t = 0; t < 5; t++) {
#pragma unroll
            for (int e = 0; e < 4; e++) {
                const uint32_t d = hsub2(xs[t][e], gm[e & 1]), h2 = hfma2(d, gh[e & 1], hmul2(d, gl[e & 1]));
                const float a = bf_lo(h2), b = bf_hi(h2);
                gate[t][e] = pack_bf16(fmaf(a, tanh_f(a), a), fmaf(b, tanh_f(b), b));
                asm volatile("" : "+r"(gate[t][e]) :: "memory");
            }
            if (TRK == 1 && t == 1) PUBLISH(3);
            if (TRK == 2 && t == 4) PUBLISH(3);
            if (TRK >= 1 && t == 4) PUBLISH(4);
        }
        if (tid == 0) TL(12);
#pragma unroll 1
        for (int t = 0; t < 5; t++) {
            const uint32_t ad = alo + ((t == 2 ? SM_O2 : ((t == 0 || t == 3) ? SM_O0 : SM_O1)) >> 4);
            mbar_wait(bars + (BAR_OF + t) * 8, 0);
            if (STAG < 5 && t == STAG && p == 1) bar_sync<5, 256>();
            wg_fence();
#pragma unroll
            for (int i = 0; i < 7; i++) {
                wgmma_ss_n80(acc2, ad + i * 256, WDESC((i + 1) * 5) + t * 128);
                if (i == 0) {
                    wg_commit(); wg_wait<1>();
                    if ((unsigned)(t - 1) < 2u && (tid & 127) == 0) mbar_arrive(bars + (BAR_OE + t + 1) * 8);
                }
                if (STAG < 5 && i == 4 && t == 4 && p == 0) asm volatile("bar.arrive 5, 256;" ::: "memory");
            }
            wg_commit();
        }
        const int wrow = m * 128 + 32 * w + p;
        {
            const uint2 sel = lds_v2(sb + SM_TOP);
            const unsigned d0 = sel.x - wrow, d1 = sel.y - wrow;
            if ((d0 & ~30u) == 0 || (d1 & ~30u) == 0) {
                mbar_wait(bars + BAR_Y * 8, 0);
#pragma unroll
                for (int h = 0; h < 2; h++) {
                    const unsigned me = 2 * r + 16 * h;
                    if (d0 == me || d1 == me) {
#pragma unroll
                        for (int t = 0; t < 5; t++) {
                            const uint32_t a = sb + SM_GT + (d0 == me ? 0 : 160) + (t < 4 ? t + odd : 4 - 4 * odd) * 32 + c * 4;
                            gate[t][h] = lds_u32(a); gate[t][2 + h] = lds_u32(a + 16);
                        }
                    }
                }
                __syncwarp();
            }
        }
        const uint32_t ssb = sb + SM_OUT + warp * 2560;
        const uint32_t laddr = ssb + (lane & 15) * 160 + (lane >> 4) * 16;
        wg_wait<0>();
        if (tid == 0) TL(1);
        if (tid == 128) TL(14);
        if (__any_sync(0xffffffffu, acc2[0] != acc2[0] || acc2[2] != acc2[2])) {
#pragma unroll
            for (int i = 0; i < 40; i++) acc2[i] = 0.f;
            const int krow = lane & 15;
#pragma unroll 1
            for (int ks = 0; ks < 40; ks++) {
                const int i = ks / 5;
                const uint32_t* src = ob + (ks - 5 * i) * 8192 + (SRC(i) - g) * 1024;
                uint32_t a0, a1, a2, a3; unsigned spins = 0;
                do { a0 = ld_relaxed_u32(src); a2 = ld_relaxed_u32(src + 32); a1 = ld_relaxed_u32(src + 64); a3 = ld_relaxed_u32(src + 96); }
                while (__any_sync(0xffffffffu, max(max(a0, a1), max(a2, a3)) == EMPTY_WORD) && ++spins < SPIN_MAX);
#pragma unroll
                for (int nb = 0; nb < 5; nb++) {
                    uint32_t b[4];
                    ldsm4t(sb + (nb < 4 ? SM_WO + ks * 2048 : SM_WT + (ks % 10) * 2048) + krow * 128 + (((2 * (nb < 4 ? nb : ks / 10) + (lane >> 4)) ^ (krow & 7)) << 4), b);
                    mma16(*reinterpret_cast<float (*)[4]>(&acc2[8 * nb]), a0, a1, a2, a3, b[0], b[1]);
                    mma16(*reinterpret_cast<float (*)[4]>(&acc2[8 * nb + 4]), a0, a1, a2, a3, b[2], b[3]);
                }
            }
        }
#pragma unroll
        for (int t = 0; t < 5; t++) {
            uint32_t o[4];
#pragma unroll
            for (int e = 0; e < 4; e++) o[e] = hadd2(xs[t][e], hmul2(pack_bf16(acc2[8 * t + 2 * e], acc2[8 * t + 2 * e + 1]), gate[t][e]));
            stsm4(laddr + (t < 4 ? t + odd : 4 - 4 * odd) * 32, o[0], o[1], o[2], o[3]);
        }
        asm volatile("fence.proxy.async.shared::cta;" ::: "memory");
        __syncwarp();
        if (elect_one()) tma3d_store(&tm_o, ssb, g * 80, m * 64 + w * 16, p);
    }
}

typedef CUresult (*EncodeFn)(CUtensorMap*, CUtensorMapDataType, cuuint32_t, void*, const cuuint64_t*, const cuuint64_t*, const cuuint32_t*,
                             const cuuint32_t*, CUtensorMapInterleave, CUtensorMapSwizzle, CUtensorMapL2promotion, CUtensorMapFloatOOBfill);

static void encode(EncodeFn enc, CUtensorMap* tm, const void* ptr, int rank, uint64_t d0, uint64_t d1, uint64_t d2, uint64_t s1, uint64_t s2,
                   uint32_t b0, uint32_t b1, uint32_t b2, CUtensorMapSwizzle swz) {
    cuuint64_t dims[3] = {d0, d1, d2}, strides[2] = {s1, s2};
    cuuint32_t box[3] = {b0, b1, b2}, es[3] = {1, 1, 1};
    enc(tm, CU_TENSOR_MAP_DATA_TYPE_BFLOAT16, rank, const_cast<void*>(ptr), dims, strides, box, es, CU_TENSOR_MAP_INTERLEAVE_NONE, swz,
        CU_TENSOR_MAP_L2_PROMOTION_L2_128B, CU_TENSOR_MAP_FLOAT_OOB_FILL_NONE);
}

}

extern "C" void kernel_launch(void* const* d_in, const int* in_sizes, int n_in, void* d_out, int out_size) {
    using namespace fk;
    (void)in_sizes; (void)n_in; (void)out_size;
    const __nv_bfloat16* x = (const __nv_bfloat16*)d_in[0];
    const __nv_bfloat16* wqkv = (const __nv_bfloat16*)d_in[1];
    const __nv_bfloat16* wo = (const __nv_bfloat16*)d_in[2];
    const __nv_bfloat16* wr = (const __nv_bfloat16*)d_in[4];
    const __nv_bfloat16* wg = (const __nv_bfloat16*)d_in[5];
    const __nv_bfloat16* wu = (const __nv_bfloat16*)d_in[6];
    const __nv_bfloat16* wd = (const __nv_bfloat16*)d_in[7];
    static EncodeFn enc = nullptr;
    static Scratch* scratch = nullptr;
    static Roles roles; static int by_sm = 0;
    if (!enc) {
        void* fn = nullptr; cudaDriverEntryPointQueryResult qr;
        cudaGetDriverEntryPoint("cuTensorMapEncodeTiled", &fn, cudaEnableDefault, &qr);
        enc = (EncodeFn)fn;
        cudaFuncSetAttribute(fused_kernel, cudaFuncAttributeMaxDynamicSharedMemorySize, SM_TOTAL);
        cudaGetSymbolAddress((void**)&scratch, g_scratch);
        int dev = 0, nsm = 0;
        cudaGetDevice(&dev); cudaDeviceGetAttribute(&nsm, cudaDevAttrMultiProcessorCount, dev);
        by_sm = nsm == NCTA + NIDLE;
        for (int t = 0; t < 66; t++) roles.pair[t] = t < 32 ? (t & 7) * 8 + (t >> 3) : (t < 60 ? (1 + (t - 32) % 7) * 8 + 4 + (t - 32) / 7 : (t < 62 ? t + 4 : t - 58));
    }
    CUtensorMap tx, tw, twt, two, td, tg, tu, to;
    encode(enc, &tx, x, 3, 640, 1024, 2, 2560, 1280, 64, 64, 2, CU_TENSOR_MAP_SWIZZLE_128B);
    encode(enc, &tw, wqkv, 3, 640, 640, 3, 3840, 1280, 64, 32, 3, CU_TENSOR_MAP_SWIZZLE_128B);
    encode(enc, &twt, wqkv, 3, 640, 640, 3, 3840, 1280, 16, 32, 3, CU_TENSOR_MAP_SWIZZLE_32B);
    encode(enc, &two, wo, 2, 640, 640, 1, 1280, 0, 64, 80, 1, CU_TENSOR_MAP_SWIZZLE_128B);
    encode(enc, &td, wd, 3, 64, 1728, 10, 1280, 128, 64, 32, 5, CU_TENSOR_MAP_SWIZZLE_128B);
    encode(enc, &to, d_out, 3, 640, 1024, 2, 2560, 1280, 80, 16, 1, CU_TENSOR_MAP_SWIZZLE_NONE);
    encode(enc, &tg, wg, 2, 1728, 640, 1, 3456, 0, 32, 80, 1, CU_TENSOR_MAP_SWIZZLE_64B);
    encode(enc, &tu, wu, 2, 1728, 640, 1, 3456, 0, 32, 80, 1, CU_TENSOR_MAP_SWIZZLE_64B);
    fused_kernel<<<NCTA + NIDLE, NTHREADS, SM_TOTAL>>>(scratch, x, wqkv, wo, wr, wd, (__nv_bfloat16*)d_out, by_sm, roles, tx, tw, twt, two, td, tg, tu, to);
}
```

```cpp
#include <cuda_runtime.h>
#include <cuda_bf16.h>
#include <cuda.h>
#include <stdint.h>

#define DEVI __device__ __forceinline__

namespace fk {

constexpr int DM = 640;
constexpr int NCTA = 128, NIDLE = 4, NTHREADS = 512;
constexpr int NAUX = 224;
constexpr int NMOE = 54;
constexpr int STAGE = 47104;
constexpr int OFF_B = 16384, B_HALF = 15360;
constexpr int SM_WO = 0;
constexpr int SM_G7 = 81920;
constexpr int SM_WT = 87040;
constexpr int SM_DW = 107520;
constexpr int SM_OUT = 136192;
constexpr int SM_EX = 3 * STAGE;
constexpr int SM_O0 = 3 * STAGE + OFF_B, SM_O1 = 4 * STAGE, SM_O2 = SM_DW;
constexpr int SM_MW = 4 * STAGE;
constexpr int SM_BX = SM_MW + 35840;
constexpr int SM_XSEL = SM_BX + 2240;
constexpr int SM_ST = SM_XSEL + 2592;
constexpr int SM_GT = SM_ST + 1152;
constexpr int SM_GU = SM_GT + 320;
constexpr int SM_H = SM_GU + 256;
constexpr int SM_TOP = SM_XSEL + 1280;
constexpr int SM_BAR = SM_H + 128;
constexpr int SM_TL = SM_BAR + 272;
constexpr int SM_TOTAL = SM_TL;
static_assert(SM_TOTAL <= 232448 && SM_BAR % 8 == 0 && SM_XSEL % 16 == 0 && SM_ST % 16 == 0 && SM_GT % 16 == 0 && SM_BX % 1024 == 0 && SM_TOP % 16 == 0, "smem layout");
constexpr int BAR_FULL = 0, BAR_EMPTY = 4, BAR_F0B = 8, BAR_Y = 9, BAR_GW = 10, BAR_DW = 11, BAR_PX = 12, BAR_RS = 13, BAR_SEL = 14,
              BAR_OF = 15  , BAR_OE = 20  , BAR_WO = 24, BAR_CS = 25, BAR_PA = 26, BAR_AE = 27  , NBAR = 33;
#define POLL_NS 100
#define PF1_NS 200
#define STAG 3
#define GP0 4
#define DP0 9
constexpr uint32_t EMPTY_WORD = 0xffffffffu;
struct Roles { unsigned short pair[NCTA / 2 + NIDLE / 2]; };
constexpr unsigned SPIN_MAX = 1u << 20;

struct Outbox {
    uint4 bx[2][3][32];
    uint4 msg[192];
    uint4 gt[2][32];
};
struct Scratch {
    uint4 o[16][5][8][256];
    uint4 halo[NCTA][320];
    unsigned flag[16][8][8];
    Outbox box[NIDLE];
    uint4 cs[8][32][64];
    uint4 yp[8][56][40];
    uint2 rowinfo[16][2][64];
    unsigned rdone[NCTA][8];
    unsigned open[NIDLE][32];
    unsigned epoch[(NCTA + NIDLE) * 32];
};
__device__ Scratch g_scratch;
#define TL(i) do { } while (0)

DEVI uint32_t smem_u32(const void* p) { return (uint32_t)__cvta_generic_to_shared(p); }
DEVI void mbar_init(uint32_t bar, uint32_t cnt) { asm volatile("mbarrier.init.shared::cta.b64 [%0], %1;" :: "r"(bar), "r"(cnt)); }
DEVI void mbar_expect_tx(uint32_t bar, uint32_t bytes) { asm volatile("mbarrier.arrive.expect_tx.shared::cta.b64 _, [%0], %1;" :: "r"(bar), "r"(bytes) : "memory"); }
DEVI void mbar_arrive(uint32_t bar) { asm volatile("mbarrier.arrive.shared::cta.b64 _, [%0];" :: "r"(bar) : "memory"); }
DEVI uint32_t clk32() { uint32_t t; asm volatile("mov.u32 %0, %%clock;" : "=r"(t) :: "memory"); return t; }
DEVI bool mbar_try(uint32_t bar, uint32_t parity) {
    uint32_t ok;
    asm volatile("{\n.reg .pred p;\nmbarrier.try_wait.parity.shared::cta.b64 p, [%1], %2, 0x989680;\nselp.u32 %0, 1, 0, p;\n}" : "=r"(ok) : "r"(bar), "r"(parity) : "memory");
    return ok != 0;
}
DEVI void mbar_wait(uint32_t bar, uint32_t parity) {
    while (!mbar_try(bar, parity)) { }
}
DEVI bool elect_one() {
    uint32_t p;
    asm volatile("{\n.reg .pred P;\nelect.sync _|P, 0xffffffff;\nselp.u32 %0, 1, 0, P;\n}" : "=r"(p));
    return p != 0;
}
DEVI void tma3d(uint32_t dst, const CUtensorMap* tm, uint32_t bar, int c0, int c1, int c2) {
    asm volatile("cp.async.bulk.tensor.3d.shared::cluster.global.mbarrier::complete_tx::bytes [%0], [%1, {%3, %4, %5}], [%2];"
                 :: "r"(dst), "l"(tm), "r"(bar), "r"(c0), "r"(c1), "r"(c2) : "memory");
}
DEVI void tma3d_mc(uint32_t dst, const CUtensorMap* tm, uint32_t bar, int c0, int c1, int c2) {
    asm volatile("cp.async.bulk.tensor.3d.shared::cluster.global.mbarrier::complete_tx::bytes.multicast::cluster [%0], [%1, {%3, %4, %5}], [%2], %6;"
                 :: "r"(dst), "l"(tm), "r"(bar), "r"(c0), "r"(c1), "r"(c2), "h"((uint16_t)3) : "memory");
}
DEVI void tma2d(uint32_t dst, const CUtensorMap* tm, uint32_t bar, int c0, int c1) {
    asm volatile("cp.async.bulk.tensor.2d.shared::cluster.global.mbarrier::complete_tx::bytes [%0], [%1, {%3, %4}], [%2];"
                 :: "r"(dst), "l"(tm), "r"(bar), "r"(c0), "r"(c1) : "memory");
}
DEVI void tma2d_prefetch(const CUtensorMap* tm, int c0, int c1) {
    asm volatile("cp.async.bulk.prefetch.tensor.2d.L2.global [%0, {%1, %2}];" :: "l"(tm), "r"(c0), "r"(c1) : "memory");
}
DEVI void tma2d_mc(uint32_t dst, const CUtensorMap* tm, uint32_t bar, int c0, int c1) {
    asm volatile("cp.async.bulk.tensor.2d.shared::cluster.global.mbarrier::complete_tx::bytes.multicast::cluster [%0], [%1, {%3, %4}], [%2], %5;"
                 :: "r"(dst), "l"(tm), "r"(bar), "r"(c0), "r"(c1), "h"((uint16_t)3) : "memory");
}
DEVI void mbar_arrive_both(uint32_t bar) {
    asm volatile("{\n.reg .b32 ra;\nmapa.shared::cluster.u32 ra, %0, 0;\nmbarrier.arrive.shared::cluster.b64 _, [ra];\n"
                 "mapa.shared::cluster.u32 ra, %0, 1;\nmbarrier.arrive.shared::cluster.b64 _, [ra];\n}" :: "r"(bar) : "memory");
}
DEVI void st_async_peer(uint32_t addr, uint32_t bar, uint32_t peer, uint32_t v) {
    asm volatile("{\n.reg .b32 ra, rb;\nmapa.shared::cluster.u32 ra, %0, %2;\nmapa.shared::cluster.u32 rb, %1, %2;\n"
                 "st.async.weak.shared::cluster.mbarrier::complete_tx::bytes.b32 [ra], %3, [rb];\n}" :: "r"(addr), "r"(bar), "r"(peer), "r"(v) : "memory");
}
DEVI void bulk_load(uint32_t dst, const void* src, uint32_t bytes, uint32_t bar) {
    asm volatile("cp.async.bulk.shared::cluster.global.mbarrier::complete_tx::bytes [%0], [%1], %2, [%3];" :: "r"(dst), "l"(src), "r"(bytes), "r"(bar) : "memory");
}
DEVI void cluster_arrive() { asm volatile("barrier.cluster.arrive.relaxed.aligned;" ::: "memory"); }
DEVI void cluster_wait() { asm volatile("barrier.cluster.wait.aligned;" ::: "memory"); }
DEVI void wg_fence() { asm volatile("wgmma.fence.sync.aligned;" ::: "memory"); }
DEVI void wg_commit() { asm volatile("wgmma.commit_group.sync.aligned;" ::: "memory"); }
template <int N> DEVI void wg_wait() { asm volatile("wgmma.wait_group.sync.aligned %0;" :: "n"(N) : "memory"); }
template <int ID, int N> DEVI void bar_sync() { asm volatile("bar.sync %0, %1;" :: "n"(ID), "n"(N) : "memory"); }
DEVI void spin_guard(unsigned& n) { if (++n > SPIN_MAX) __trap(); }
DEVI uint4 ld_relaxed_v4(const void* p) {
    uint4 v;
    asm volatile("ld.relaxed.gpu.global.v4.u32 {%0,%1,%2,%3}, [%4];" : "=r"(v.x), "=r"(v.y), "=r"(v.z), "=r"(v.w) : "l"(p) : "memory");
    return v;
}
DEVI void st_relaxed_v4(void* p, const uint4& v) {
    asm volatile("st.relaxed.gpu.global.v4.u32 [%0], {%1,%2,%3,%4};" :: "l"(p), "r"(v.x), "r"(v.y), "r"(v.z), "r"(v.w) : "memory");
}
DEVI unsigned ld_relaxed_u32(const void* p) { unsigned v; asm volatile("ld.relaxed.gpu.global.u32 %0, [%1];" : "=r"(v) : "l"(p) : "memory"); return v; }
DEVI unsigned ld_acquire_u32(const void* p) { unsigned v; asm volatile("ld.acquire.gpu.global.u32 %0, [%1];" : "=r"(v) : "l"(p) : "memory"); return v; }
DEVI void st_relaxed_u32(void* p, unsigned v) { asm volatile("st.relaxed.gpu.global.u32 [%0], %1;" :: "l"(p), "r"(v) : "memory"); }
DEVI void st_relaxed_v2(void* p, unsigned a, unsigned b) { asm volatile("st.relaxed.gpu.global.v2.u32 [%0], {%1,%2};" :: "l"(p), "r"(a), "r"(b) : "memory"); }
DEVI uint4 ld_gen_v4(const void* p) {
    uint4 v;
    asm volatile("ld.relaxed.gpu.v4.u32 {%0,%1,%2,%3}, [%4];" : "=r"(v.x), "=r"(v.y), "=r"(v.z), "=r"(v.w) : "l"(p) : "memory");
    return v;
}
DEVI void st_gen_v4(void* p, const uint4& v) { asm volatile("st.relaxed.gpu.v4.u32 [%0], {%1,%2,%3,%4};" :: "l"(p), "r"(v.x), "r"(v.y), "r"(v.z), "r"(v.w) : "memory"); }
DEVI float sqrt_approx(float x) { float y; asm("sqrt.approx.ftz.f32 %0, %1;" : "=f"(y) : "f"(x)); return y; }
DEVI void red_add_u32(unsigned* p, unsigned v) { asm volatile("red.relaxed.gpu.global.add.u32 [%0], %1;" :: "l"(p), "r"(v) : "memory"); }
DEVI void red_add_v4(void* p, float a, float b, float c, float d) {
    asm volatile("red.relaxed.gpu.global.add.v4.f32 [%0], {%1,%2,%3,%4};" :: "l"(p), "f"(a), "f"(b), "f"(c), "f"(d) : "memory");
}
DEVI float4 ld_relaxed_f4(const void* p) {
    float4 v;
    asm volatile("ld.relaxed.gpu.global.v4.f32 {%0,%1,%2,%3}, [%4];" : "=f"(v.x), "=f"(v.y), "=f"(v.z), "=f"(v.w) : "l"(p) : "memory");
    return v;
}
DEVI void tma3d_store(const CUtensorMap* tm, uint32_t src, int c0, int c1, int c2) {
    asm volatile("cp.async.bulk.tensor.3d.global.shared::cta.bulk_group [%0, {%2, %3, %4}], [%1];\ncp.async.bulk.commit_group;\ncp.async.bulk.wait_group.read 0;"
                 :: "l"(tm), "r"(src), "r"(c0), "r"(c1), "r"(c2) : "memory");
}
DEVI uint32_t lds_u16(uint32_t a) { unsigned short v; asm volatile("ld.shared.u16 %0, [%1];" : "=h"(v) : "r"(a)); return v; }
DEVI void fence_gpu() { asm volatile("fence.acq_rel.gpu;" ::: "memory"); }
DEVI uint4 ldg_v4(const void* p) {
    uint4 v;
    asm volatile("ld.global.L1::no_allocate.v4.u32 {%0,%1,%2,%3}, [%4];" : "=r"(v.x), "=r"(v.y), "=r"(v.z), "=r"(v.w) : "l"(p) : "memory");
    return v;
}
DEVI uint4 lds_v4(uint32_t a) { uint4 v; asm volatile("ld.shared.v4.u32 {%0,%1,%2,%3}, [%4];" : "=r"(v.x), "=r"(v.y), "=r"(v.z), "=r"(v.w) : "r"(a)); return v; }
DEVI void sts_v4(uint32_t a, const uint4& v) { asm volatile("st.shared.v4.u32 [%0], {%1,%2,%3,%4};" :: "r"(a), "r"(v.x), "r"(v.y), "r"(v.z), "r"(v.w) : "memory"); }
DEVI void sts_f4(uint32_t a, float x, float y, float z, float w) { asm volatile("st.shared.v4.f32 [%0], {%1,%2,%3,%4};" :: "r"(a), "f"(x), "f"(y), "f"(z), "f"(w) : "memory"); }
DEVI float2 lds_f2(uint32_t a) { float2 v; asm volatile("ld.shared.v2.f32 {%0,%1}, [%2];" : "=f"(v.x), "=f"(v.y) : "r"(a)); return v; }
DEVI float4 lds_f4(uint32_t a) { float4 v; asm volatile("ld.shared.v4.f32 {%0,%1,%2,%3}, [%4];" : "=f"(v.x), "=f"(v.y), "=f"(v.z), "=f"(v.w) : "r"(a)); return v; }
DEVI void ldsm4(uint32_t addr, uint32_t& a, uint32_t& b, uint32_t& c, uint32_t& d) {
    asm volatile("ldmatrix.sync.aligned.m8n8.x4.shared.b16 {%0,%1,%2,%3}, [%4];" : "=r"(a), "=r"(b), "=r"(c), "=r"(d) : "r"(addr));
}
DEVI void ldsm4_if(bool on, uint32_t addr, uint32_t (&v)[4]) {
    asm volatile("{\n.reg .pred p;\nsetp.ne.b32 p, %5, 0;\n@p ldmatrix.sync.aligned.m8n8.x4.shared.b16 {%0,%1,%2,%3}, [%4];\n}"
                 : "+r"(v[0]), "+r"(v[1]), "+r"(v[2]), "+r"(v[3]) : "r"(addr), "r"((uint32_t)on));
}
DEVI void ldsm4t(uint32_t addr, uint32_t (&v)[4]) {
    asm volatile("ldmatrix.sync.aligned.m8n8.x4.trans.shared.b16 {%0,%1,%2,%3}, [%4];" : "=r"(v[0]), "=r"(v[1]), "=r"(v[2]), "=r"(v[3]) : "r"(addr));
}
DEVI void ldsm2(uint32_t addr, uint32_t& a, uint32_t& b) { asm volatile("ldmatrix.sync.aligned.m8n8.x2.shared.b16 {%0,%1}, [%2];" : "=r"(a), "=r"(b) : "r"(addr)); }
DEVI void cp_async16(uint32_t dst, const void* src) { asm volatile("cp.async.cg.shared.global [%0], [%1], 16;" :: "r"(dst), "l"(src) : "memory"); }
DEVI void prefetch_l2_bulk(const void* p, uint32_t bytes) { asm volatile("cp.async.bulk.prefetch.L2.global [%0], %1;" :: "l"(p), "r"(bytes) : "memory"); }
DEVI void sts_u16(uint32_t a, uint32_t v) { asm volatile("st.shared.u16 [%0], %1;" :: "r"(a), "h"((unsigned short)v) : "memory"); }
DEVI uint32_t hfma2(uint32_t a, uint32_t b, uint32_t c) { uint32_t d; asm("fma.rn.bf16x2 %0, %1, %2, %3;" : "=r"(d) : "r"(a), "r"(b), "r"(c)); return d; }
DEVI float tanh_f(float x) { float t; asm("tanh.approx.f32 %0, %1;" : "=f"(t) : "f"(x)); return t; }
DEVI void stsm4(uint32_t addr, uint32_t a, uint32_t b, uint32_t c, uint32_t d) {
    asm volatile("stmatrix.sync.aligned.m8n8.x4.shared.b16 [%0], {%1,%2,%3,%4};" :: "r"(addr), "r"(a), "r"(b), "r"(c), "r"(d) : "memory");
}
DEVI uint32_t movm(uint32_t a) { uint32_t d; asm("movmatrix.sync.aligned.m8n8.trans.b16 %0, %1;" : "=r"(d) : "r"(a)); return d; }
DEVI void mma16(float (&c)[4], uint32_t a0, uint32_t a1, uint32_t a2, uint32_t a3, uint32_t b0, uint32_t b1) {
    asm("mma.sync.aligned.m16n8k16.row.col.f32.bf16.bf16.f32 {%0,%1,%2,%3}, {%4,%5,%6,%7}, {%8,%9}, {%0,%1,%2,%3};"
                 : "+f"(c[0]), "+f"(c[1]), "+f"(c[2]), "+f"(c[3]) : "r"(a0), "r"(a1), "r"(a2), "r"(a3), "r"(b0), "r"(b1));
}
DEVI void mma8(float (&c)[4], uint32_t a0, uint32_t a1, uint32_t b0) {
    asm("mma.sync.aligned.m16n8k8.row.col.f32.bf16.bf16.f32 {%0,%1,%2,%3}, {%4,%5}, {%6}, {%0,%1,%2,%3};"
                 : "+f"(c[0]), "+f"(c[1]), "+f"(c[2]), "+f"(c[3]) : "r"(a0), "r"(a1), "r"(b0));
}
DEVI uint32_t pack_bf16(float lo, float hi) { uint32_t d; asm("cvt.rn.bf16x2.f32 %0, %1, %2;" : "=r"(d) : "f"(hi), "f"(lo)); return d; }
DEVI float bf_lo(uint32_t v) { return __uint_as_float(v << 16); }
DEVI float bf_hi(uint32_t v) { return __uint_as_float(v & 0xffff0000u); }
DEVI float bfr(float x) { return __bfloat162float(__float2bfloat16_rn(x)); }
DEVI uint32_t tagf(float v, unsigned tag) { return (__float_as_uint(v) & ~15u) | (tag & 15); }
DEVI float ex2(float x) { float y; asm("ex2.approx.ftz.f32 %0, %1;" : "=f"(y) : "f"(x)); return y; }
DEVI float rcp(float x) { float y; asm("rcp.approx.ftz.f32 %0, %1;" : "=f"(y) : "f"(x)); return y; }
DEVI float sigmoid_f(float x) { return rcp(1.0f + ex2(x * -1.4426950408889634f)); }
DEVI float silu_f(float x) { const float h = 0.5f * x; float t; asm("tanh.approx.f32 %0, %1;" : "=f"(t) : "f"(h)); return fmaf(h, t, h); }
DEVI uint32_t hsub2(uint32_t a, uint32_t b) { uint32_t d; asm("sub.rn.bf16x2 %0, %1, %2;" : "=r"(d) : "r"(a), "r"(b)); return d; }
DEVI uint32_t hadd2(uint32_t a, uint32_t b) { uint32_t d; asm("add.rn.bf16x2 %0, %1, %2;" : "=r"(d) : "r"(a), "r"(b)); return d; }
DEVI uint32_t hmul2(uint32_t a, uint32_t b) { uint32_t d; asm("mul.rn.bf16x2 %0, %1, %2;" : "=r"(d) : "r"(a), "r"(b)); return d; }
DEVI uint32_t dup_hi(float x) { return __byte_perm(__float_as_uint(x), 0, 0x3232); }
DEVI void sts_u32(uint32_t a, uint32_t v) { asm volatile("st.shared.u32 [%0], %1;" :: "r"(a), "r"(v) : "memory"); }
DEVI void sts_f2(uint32_t a, float x, float y) { asm volatile("st.shared.v2.f32 [%0], {%1,%2};" :: "r"(a), "f"(x), "f"(y) : "memory"); }
DEVI uint2 lds_v2(uint32_t a) { uint2 v; asm volatile("ld.shared.v2.u32 {%0,%1}, [%2];" : "=r"(v.x), "=r"(v.y) : "r"(a)); return v; }
DEVI uint32_t lds_u32(uint32_t a) { uint32_t v; asm volatile("ld.shared.u32 %0, [%1];" : "=r"(v) : "r"(a)); return v; }
DEVI float lds_f32(uint32_t a) { float v; asm volatile("ld.shared.f32 %0, [%1];" : "=f"(v) : "r"(a)); return v; }
DEVI float shfl_x(float v, int o) { return __shfl_xor_sync(0xffffffffu, v, o); }

DEVI void wgmma_rs_n192(float (&d)[120], uint32_t a0, uint32_t a1, uint32_t a2, uint32_t a3, uint32_t blo, uint32_t scale_d) {
    asm volatile("{\n.reg .b64 db;\n.reg .pred p;\n"
        "setp.ne.b32 p, %101, 0;\n"
        "mov.b64 db, {%100, 0x40000040};\n"
        "wgmma.mma_async.sync.aligned.m64n192k16.f32.bf16.bf16 "
        "{%0, %1, %2, %3, %4, %5, %6, %7, %8, %9, %10, %11, %12, %13, %14, %15, %16, %17, %18, %19, %20, %21, %22, %23, %24, %25, %26, %27, %28, %29, %30, %31, %32, %33, %34, %35, %36, %37, %38, %39, %40, %41, %42, %43, %44, %45, %46, %47, %48, %49, %50, %51, %52, %53, %54, %55, %56, %57, %58, %59, %60, %61, %62, %63, %64, %65, %66, %67, %68, %69, %70, %71, %72, %73, %74, %75, %76, %77, %78, %79, %80, %81, %82, %83, %84, %85, %86, %87, %88, %89, %90, %91, %92, %93, %94, %95}, "
        "{%96, %97, %98, %99}, db, p, 1, 1, 1;\n}\n"
        : "+f"(d[0]), "+f"(d[1]), "+f"(d[2]), "+f"(d[3]), "+f"(d[4]), "+f"(d[5]), "+f"(d[6]), "+f"(d[7]), "+f"(d[8]), "+f"(d[9]), "+f"(d[10]), "+f"(d[11]), "+f"(d[12]), "+f"(d[13]), "+f"(d[14]), "+f"(d[15]), "+f"(d[16]), "+f"(d[17]), "+f"(d[18]), "+f"(d[19]), "+f"(d[20]), "+f"(d[21]), "+f"(d[22]), "+f"(d[23]), "+f"(d[24]), "+f"(d[25]), "+f"(d[26]), "+f"(d[27]), "+f"(d[28]), "+f"(d[29]), "+f"(d[30]), "+f"(d[31]), "+f"(d[32]), "+f"(d[33]), "+f"(d[34]), "+f"(d[35]), "+f"(d[36]), "+f"(d[37]), "+f"(d[38]), "+f"(d[39]), "+f"(d[40]), "+f"(d[41]), "+f"(d[42]), "+f"(d[43]), "+f"(d[44]), "+f"(d[45]), "+f"(d[46]), "+f"(d[47]), "+f"(d[48]), "+f"(d[49]), "+f"(d[50]), "+f"(d[51]), "+f"(d[52]), "+f"(d[53]), "+f"(d[54]), "+f"(d[55]), "+f"(d[56]), "+f"(d[57]), "+f"(d[58]), "+f"(d[59]), "+f"(d[60]), "+f"(d[61]), "+f"(d[62]), "+f"(d[63]), "+f"(d[64]), "+f"(d[65]), "+f"(d[66]), "+f"(d[67]), "+f"(d[68]), "+f"(d[69]), "+f"(d[70]), "+f"(d[71]), "+f"(d[72]), "+f"(d[73]), "+f"(d[74]), "+f"(d[75]), "+f"(d[76]), "+f"(d[77]), "+f"(d[78]), "+f"(d[79]), "+f"(d[80]), "+f"(d[81]), "+f"(d[82]), "+f"(d[83]), "+f"(d[84]), "+f"(d[85]), "+f"(d[86]), "+f"(d[87]), "+f"(d[88]), "+f"(d[89]), "+f"(d[90]), "+f"(d[91]), "+f"(d[92]), "+f"(d[93]), "+f"(d[94]), "+f"(d[95])
        : "r"(a0), "r"(a1), "r"(a2), "r"(a3), "r"(blo), "r"(scale_d));
}
DEVI void wgmma_rs_n48(float (&d)[120], uint32_t a0, uint32_t a1, uint32_t a2, uint32_t a3, uint32_t blo, uint32_t scale_d) {
    asm volatile("{\n.reg .b64 db;\n.reg .pred p;\n"
        "setp.ne.b32 p, %29, 0;\n"
        "mov.b64 db, {%28, 0xc0000010};\n"
        "wgmma.mma_async.sync.aligned.m64n48k16.f32.bf16.bf16 "
        "{%0, %1, %2, %3, %4, %5, %6, %7, %8, %9, %10, %11, %12, %13, %14, %15, %16, %17, %18, %19, %20, %21, %22, %23}, "
        "{%24, %25, %26, %27}, db, p, 1, 1, 1;\n}\n"
        : "+f"(d[96]), "+f"(d[97]), "+f"(d[98]), "+f"(d[99]), "+f"(d[100]), "+f"(d[101]), "+f"(d[102]), "+f"(d[103]), "+f"(d[104]), "+f"(d[105]), "+f"(d[106]), "+f"(d[107]), "+f"(d[108]), "+f"(d[109]), "+f"(d[110]), "+f"(d[111]), "+f"(d[112]), "+f"(d[113]), "+f"(d[114]), "+f"(d[115]), "+f"(d[116]), "+f"(d[117]), "+f"(d[118]), "+f"(d[119])
        : "r"(a0), "r"(a1), "r"(a2), "r"(a3), "r"(blo), "r"(scale_d));
}
DEVI void wgmma_rs_n192x(float (&d)[120], uint32_t a0, uint32_t a1, uint32_t a2, uint32_t a3, uint32_t blo) {
    asm volatile("{\n.reg .b64 db;\n.reg .pred p;\n"
        "mov.b64 db, {%100, 0x40000000};\n"
        "wgmma.mma_async.sync.aligned.m64n192k16.f32.bf16.bf16 "
        "{%0, %1, %2, %3, %4, %5, %6, %7, %8, %9, %10, %11, %12, %13, %14, %15, %16, %17, %18, %19, %20, %21, %22, %23, %24, %25, %26, %27, %28, %29, %30, %31, %32, %33, %34, %35, %36, %37, %38, %39, %40, %41, %42, %43, %44, %45, %46, %47, %48, %49, %50, %51, %52, %53, %54, %55, %56, %57, %58, %59, %60, %61, %62, %63, %64, %65, %66, %67, %68, %69, %70, %71, %72, %73, %74, %75, %76, %77, %78, %79, %80, %81, %82, %83, %84, %85, %86, %87, %88, %89, %90, %91, %92, %93, %94, %95}, "
        "{%96, %97, %98, %99}, db, 1, 1, 1, 1;\n}\n"
        : "+f"(d[0]), "+f"(d[1]), "+f"(d[2]), "+f"(d[3]), "+f"(d[4]), "+f"(d[5]), "+f"(d[6]), "+f"(d[7]), "+f"(d[8]), "+f"(d[9]), "+f"(d[10]), "+f"(d[11]), "+f"(d[12]), "+f"(d[13]), "+f"(d[14]), "+f"(d[15]), "+f"(d[16]), "+f"(d[17]), "+f"(d[18]), "+f"(d[19]), "+f"(d[20]), "+f"(d[21]), "+f"(d[22]), "+f"(d[23]), "+f"(d[24]), "+f"(d[25]), "+f"(d[26]), "+f"(d[27]), "+f"(d[28]), "+f"(d[29]), "+f"(d[30]), "+f"(d[31]), "+f"(d[32]), "+f"(d[33]), "+f"(d[34]), "+f"(d[35]), "+f"(d[36]), "+f"(d[37]), "+f"(d[38]), "+f"(d[39]), "+f"(d[40]), "+f"(d[41]), "+f"(d[42]), "+f"(d[43]), "+f"(d[44]), "+f"(d[45]), "+f"(d[46]), "+f"(d[47]), "+f"(d[48]), "+f"(d[49]), "+f"(d[50]), "+f"(d[51]), "+f"(d[52]), "+f"(d[53]), "+f"(d[54]), "+f"(d[55]), "+f"(d[56]), "+f"(d[57]), "+f"(d[58]), "+f"(d[59]), "+f"(d[60]), "+f"(d[61]), "+f"(d[62]), "+f"(d[63]), "+f"(d[64]), "+f"(d[65]), "+f"(d[66]), "+f"(d[67]), "+f"(d[68]), "+f"(d[69]), "+f"(d[70]), "+f"(d[71]), "+f"(d[72]), "+f"(d[73]), "+f"(d[74]), "+f"(d[75]), "+f"(d[76]), "+f"(d[77]), "+f"(d[78]), "+f"(d[79]), "+f"(d[80]), "+f"(d[81]), "+f"(d[82]), "+f"(d[83]), "+f"(d[84]), "+f"(d[85]), "+f"(d[86]), "+f"(d[87]), "+f"(d[88]), "+f"(d[89]), "+f"(d[90]), "+f"(d[91]), "+f"(d[92]), "+f"(d[93]), "+f"(d[94]), "+f"(d[95])
        : "r"(a0), "r"(a1), "r"(a2), "r"(a3), "r"(blo));
}
DEVI void wgmma_rs_n48x(float (&d)[120], uint32_t a0, uint32_t a1, uint32_t a2, uint32_t a3, uint32_t blo) {
    asm volatile("{\n.reg .b64 db;\n.reg .pred p;\n"
        "mov.b64 db, {%28, 0xc0000000};\n"
        "wgmma.mma_async.sync.aligned.m64n48k16.f32.bf16.bf16 "
        "{%0, %1, %2, %3, %4, %5, %6, %7, %8, %9, %10, %11, %12, %13, %14, %15, %16, %17, %18, %19, %20, %21, %22, %23}, "
        "{%24, %25, %26, %27}, db, 1, 1, 1, 1;\n}\n"
        : "+f"(d[96]), "+f"(d[97]), "+f"(d[98]), "+f"(d[99]), "+f"(d[100]), "+f"(d[101]), "+f"(d[102]), "+f"(d[103]), "+f"(d[104]), "+f"(d[105]), "+f"(d[106]), "+f"(d[107]), "+f"(d[108]), "+f"(d[109]), "+f"(d[110]), "+f"(d[111]), "+f"(d[112]), "+f"(d[113]), "+f"(d[114]), "+f"(d[115]), "+f"(d[116]), "+f"(d[117]), "+f"(d[118]), "+f"(d[119])
        : "r"(a0), "r"(a1), "r"(a2), "r"(a3), "r"(blo));
}
DEVI void wgmma_rs_n80(float (&d)[40], uint32_t a0, uint32_t a1, uint32_t a2, uint32_t a3, uint32_t blo, uint32_t scale_d) {
    asm volatile("{\n.reg .b64 db;\n.reg .pred p;\n"
        "setp.ne.b32 p, %45, 0;\n"
        "mov.b64 db, {%44, 0x40000040};\n"
        "wgmma.mma_async.sync.aligned.m64n80k16.f32.bf16.bf16 "
        "{%0, %1, %2, %3, %4, %5, %6, %7, %8, %9, %10, %11, %12, %13, %14, %15, %16, %17, %18, %19, %20, %21, %22, %23, %24, %25, %26, %27, %28, %29, %30, %31, %32, %33, %34, %35, %36, %37, %38, %39}, "
        "{%40, %41, %42, %43}, db, p, 1, 1, 1;\n}\n"
        : "+f"(d[0]), "+f"(d[1]), "+f"(d[2]), "+f"(d[3]), "+f"(d[4]), "+f"(d[5]), "+f"(d[6]), "+f"(d[7]), "+f"(d[8]), "+f"(d[9]), "+f"(d[10]), "+f"(d[11]), "+f"(d[12]), "+f"(d[13]), "+f"(d[14]), "+f"(d[15]), "+f"(d[16]), "+f"(d[17]), "+f"(d[18]), "+f"(d[19]), "+f"(d[20]), "+f"(d[21]), "+f"(d[22]), "+f"(d[23]), "+f"(d[24]), "+f"(d[25]), "+f"(d[26]), "+f"(d[27]), "+f"(d[28]), "+f"(d[29]), "+f"(d[30]), "+f"(d[31]), "+f"(d[32]), "+f"(d[33]), "+f"(d[34]), "+f"(d[35]), "+f"(d[36]), "+f"(d[37]), "+f"(d[38]), "+f"(d[39])
        : "r"(a0), "r"(a1), "r"(a2), "r"(a3), "r"(blo), "r"(scale_d));
}
DEVI void wgmma_ss_n80(float (&d)[40], uint32_t alo, uint32_t blo) {
    asm volatile("{\n.reg .b64 da, db;\n"
        "mov.b64 da, {%40, 0x10};\n"
        "mov.b64 db, {%41, 0x40000040};\n"
        "wgmma.mma_async.sync.aligned.m64n80k16.f32.bf16.bf16 "
        "{%0, %1, %2, %3, %4, %5, %6, %7, %8, %9, %10, %11, %12, %13, %14, %15, %16, %17, %18, %19, %20, %21, %22, %23, %24, %25, %26, %27, %28, %29, %30, %31, %32, %33, %34, %35, %36, %37, %38, %39}, "
        "da, db, 1, 1, 1, 0, 1;\n}\n"
        : "+f"(d[0]), "+f"(d[1]), "+f"(d[2]), "+f"(d[3]), "+f"(d[4]), "+f"(d[5]), "+f"(d[6]), "+f"(d[7]), "+f"(d[8]), "+f"(d[9]), "+f"(d[10]), "+f"(d[11]), "+f"(d[12]), "+f"(d[13]), "+f"(d[14]), "+f"(d[15]), "+f"(d[16]), "+f"(d[17]), "+f"(d[18]), "+f"(d[19]), "+f"(d[20]), "+f"(d[21]), "+f"(d[22]), "+f"(d[23]), "+f"(d[24]), "+f"(d[25]), "+f"(d[26]), "+f"(d[27]), "+f"(d[28]), "+f"(d[29]), "+f"(d[30]), "+f"(d[31]), "+f"(d[32]), "+f"(d[33]), "+f"(d[34]), "+f"(d[35]), "+f"(d[36]), "+f"(d[37]), "+f"(d[38]), "+f"(d[39])
        : "r"(alo), "r"(blo));
}

DEVI unsigned redux_max(unsigned v) { return __reduce_max_sync(0xffffffffu, v); }

DEVI void service_cta(Scratch* __restrict__ sc, const __nv_bfloat16* __restrict__ x, uint32_t sb, int h, int tid) {
    const int warp = tid >> 5, lane = tid & 31;
    Outbox* const box = &sc->box[h];
    const unsigned tag = ld_relaxed_u32(&sc->epoch[(NCTA + h) * 32]) + 1;
    if (tid < 448) st_relaxed_v4(&box->bx[0][0][0] + tid, make_uint4(EMPTY_WORD, EMPTY_WORD, EMPTY_WORD, EMPTY_WORD));
    __syncthreads();
    unsigned spins = 0;
    if (warp == 15) {
        fence_gpu();
        if (lane < 2) st_relaxed_v4(&sc->open[h][lane * 4], make_uint4(tag, tag, tag, tag));
    } else if (warp < 8) {
        const uint4* src = &sc->cs[2 * h][0][0] + (tid >> 6) * 1024;
        uint4 v[16];
#pragma unroll
        for (int j = 0; j < 16; j++) v[j].x = tag - 1;
        while (true) {
            unsigned bad = 0;
#pragma unroll
            for (int j = 0; j < 16; j++) if ((v[j].x ^ tag) & 15) v[j] = ld_relaxed_v4(src + j * 64 + (tid & 63));
            __syncwarp();
#pragma unroll
            for (int j = 0; j < 16; j++) bad |= v[j].x ^ tag;
            if (__all_sync(0xffffffffu, (bad & 15) == 0)) break;
            if (spins == 0) while (!__any_sync(0xffffffffu, ((ld_relaxed_u32(src + (lane & 15) * 64 + 63) ^ tag) & 15) == 0)) { __nanosleep(100); spin_guard(spins); }
            spin_guard(spins);
        }
        if (tid == 0) TL(0);
        float s[8];
#pragma unroll
        for (int e = 0; e < 4; e++) {
            s[e] = 0.f;
#pragma unroll
            for (int j = 0; j < 16; j++) s[e] += __uint_as_float((&v[j].x)[e]);
        }
        sts_f4(sb + tid * 16, s[0], s[1], s[2], s[3]);
        bar_sync<1, 256>();
        if (warp < 2) {
            const uint32_t a = sb + warp * 2048 + lane * 32;
            const float4 a0 = lds_f4(a), a1 = lds_f4(a + 16), b0 = lds_f4(a + 1024), b1 = lds_f4(a + 1040);
            s[0] = a0.x + b0.x; s[1] = a0.y + b0.y; s[2] = a0.z + b0.z; s[3] = a0.w + b0.w; s[4] = a1.x + b1.x; s[5] = a1.y + b1.y; s[6] = a1.z + b1.z; s[7] = a1.w + b1.w;
#pragma unroll
            for (int row = 0; row < 3; row++) {
                uint32_t o[4];
#pragma unroll
                for (int e = 0; e < 4; e++) { o[e] = pack_bf16(s[2 * e], s[2 * e + 1]); s[2 * e] -= bf_lo(o[e]); s[2 * e + 1] -= bf_hi(o[e]); }
                st_relaxed_v4(&box->bx[warp][row][lane], make_uint4(o[0], o[1], o[2], o[3]));
            }
            if (tid == 0) TL(1);
        }
    } else if (warp < 12) {
        const int t = tid - 256;
        uint4 q[8];
        const uint4* src = reinterpret_cast<const uint4*>(&sc->rowinfo[0][0][0]) + t;
#pragma unroll
        for (int j = 0; j < 8; j++) q[j].y = q[j].w = tag - 1;
        while (true) {
            unsigned bad = 0;
#pragma unroll
            for (int j = 0; j < 8; j++) if (((q[j].y ^ tag) | (q[j].w ^ tag)) & 31) q[j] = ld_relaxed_v4(src + 128 * j);
            __syncwarp();
#pragma unroll
            for (int j = 0; j < 8; j++) bad |= (q[j].y ^ tag) | (q[j].w ^ tag);
            if (__all_sync(0xffffffffu, (bad & 31) == 0)) break;
            if (spins == 0) while (!__any_sync(0xffffffffu, ((ld_relaxed_v4(src).y ^ tag) & 31) == 0)) { __nanosleep(100); spin_guard(spins); }
            spin_guard(spins);
        }
        if (t == 0) TL(2);
        unsigned a = 0, b = 0;
#pragma unroll
        for (int j = 0; j < 8; j++) { b = max(b, min(a, q[j].y)); a = max(a, q[j].y); b = max(b, min(a, q[j].w)); a = max(a, q[j].w); }
        unsigned k1 = redux_max(a), k2 = redux_max(a == k1 ? b : a);
        if (lane == 0) sts_f2(sb + 8192 + (warp - 8) * 8, __uint_as_float(k1), __uint_as_float(k2));
        bar_sync<2, 128>();
        a = lds_u32(sb + 8192 + (lane & 7) * 4);
        k1 = redux_max(a); k2 = redux_max(a == k1 ? 0u : a);
        if (t < 80) {
            uint4 xq[2]; unsigned info[2];
#pragma unroll
            for (int tk = 0; tk < 2; tk++) {
                const int sel = 2047 - (((tk ? k2 : k1) >> 5) & 2047);
                xq[tk] = ldg_v4(reinterpret_cast<const uint4*>(x + sel * DM) + t);
                info[tk] = ld_relaxed_u32(&sc->rowinfo[sel >> 7][sel & 1][(sel & 127) >> 1]);
            }
#pragma unroll
            for (int tk = 0; tk < 2; tk++) {
                const uint32_t mm = __byte_perm(info[tk], 0, 0x1010);
                const float rs = 1.0f / bf_hi(info[tk]);
                uint32_t o[4];
#pragma unroll
                for (int e = 0; e < 4; e++) { const uint32_t d = hsub2((&xq[tk].x)[e], mm); o[e] = pack_bf16(bf_lo(d) * rs, bf_hi(d) * rs); }
                st_relaxed_v4(&box->msg[tk * 81 + t], make_uint4(o[0], o[1], o[2], o[3]));
                sts_v4(sb + SM_XSEL + tk * 1296 + t * 16, make_uint4(o[0], o[1], o[2], o[3]));
            }
        } else if (t == 96) {
            const uint4 top = make_uint4(2047 - ((k1 >> 5) & 2047), 2047 - ((k2 >> 5) & 2047), k1, k2);
            st_relaxed_v4(&box->msg[80], top); sts_v4(sb + SM_TOP, top);
        }
        if (t == 0) TL(3);
    }
    __syncthreads();
    const uint4* src = &sc->yp[2 * h + (warp >> 3)][warp & 7][0];
    uint4 v[7]; unsigned u[7];
#pragma unroll
    for (int j = 0; j < 7; j++) v[j].x = u[j] = (j == 6 && (warp & 7) >= 6) ? tag : tag - 1;
    spins = 0;
    while (NMOE) {
        unsigned bad = 0;
#pragma unroll
        for (int j = 0; j < 7; j++)
            if (((v[j].x ^ tag) | (u[j] ^ tag)) & 15) { v[j] = ld_relaxed_v4(src + j * 320 + lane); u[j] = ld_relaxed_u32(reinterpret_cast<const unsigned*>(src + j * 320 + 32) + lane); }
        __syncwarp();
#pragma unroll
        for (int j = 0; j < 7; j++) bad |= (v[j].x ^ tag) | (u[j] ^ tag);
        if (__all_sync(0xffffffffu, (bad & 15) == 0)) break;
        if (spins == 0) while (!__any_sync(0xffffffffu, ((ld_relaxed_u32(src + min(lane & 7, 5) * 320 + 32) ^ tag) & 15) == 0)) { __nanosleep(100); spin_guard(spins); }
        spin_guard(spins);
    }
    if (tid == 0) TL(4);
    float y[5] = {0.f, 0.f, 0.f, 0.f, 0.f};
#pragma unroll
    for (int j = 0; j < 7; j++) {
        if (NMOE && (j < 6 || (warp & 7) < 6)) {
            y[0] += __uint_as_float(v[j].x); y[1] += __uint_as_float(v[j].y); y[2] += __uint_as_float(v[j].z); y[3] += __uint_as_float(v[j].w); y[4] += __uint_as_float(u[j]);
        }
    }
#pragma unroll
    for (int e = 0; e < 5; e++) sts_u32(sb + (warp * 160 + e * 32 + lane) * 4, __float_as_uint(y[e]));
    __syncthreads();
    if (warp < 10) {
        const int gi = warp >= 5, e = warp - 5 * gi, tk = lane & 1, col = e * 16 + (lane >> 2) + 4 * (lane & 2);
        float sum = 0.f;
#pragma unroll
        for (int j = 0; j < 8; j++) sum += lds_f32(sb + ((gi * 8 + j) * 160 + e * 32 + lane) * 4);
        const uint32_t ks = lds_u32(sb + SM_TOP + 8 + tk * 4) >> 16;
        const float sg = bfr(sigmoid_f(__uint_as_float(((ks & 0x8000u) ? (ks & 0x7fffu) : (ks ^ 0xffffu)) << 16)));
        sts_u16(sb + 16384 + gi * 512 + tk * 160 + col * 2,
                pack_bf16(silu_f(bfr(bf_lo(lds_u16(sb + SM_XSEL + tk * 1296 + ((2 * h + gi) * 80 + col) * 2)) + bfr(bfr(sum) * sg))), 0.f));
        bar_sync<1, 320>();
        if (warp < 2 && lane < 20) st_relaxed_v4(&box->gt[warp][lane], lds_v4(sb + 16384 + tid * 16));
    }
    if (tid == 0) { st_relaxed_u32(&sc->epoch[(NCTA + h) * 32], tag); TL(5); }
}

template <int ODD, int HALF> DEVI void pack_kv(const float (&acc)[120], uint32_t (&K)[10][2], uint32_t (&V)[10][2]) {
#pragma unroll
    for (int b = 0; b < 10; b++) {
        const int pb = ODD ? (b + 8) % 10 : b, jk = pb < 8 ? 8 + pb : 18 + pb, jv = pb < 8 ? 16 + pb : 20 + pb;
        V[b][HALF] = movm(pack_bf16(acc[4 * jv + 2 * HALF], acc[4 * jv + 2 * HALF + 1]));
        K[b][HALF] = pack_bf16(acc[4 * jk + 2 * HALF], acc[4 * jk + 2 * HALF + 1]);
    }
}
template <int ODD> DEVI void pack_q(const float (&acc)[120], uint32_t (&Q)[10][2]) {
#pragma unroll
    for (int b = 0; b < 10; b++) {
        const int pb = ODD ? (b + 8) % 10 : b, jq = pb < 8 ? pb : 16 + pb;
        Q[b][0] = pack_bf16(acc[4 * jq], acc[4 * jq + 1]); Q[b][1] = pack_bf16(acc[4 * jq + 2], acc[4 * jq + 3]);
    }
}

constexpr int KROT = 5;
#define WOP 8
#define SIDE_N 0
#define RS_PACE(t) (t)
#define SRC(i) ((i) == 0 ? g : ((i) - 1 < g ? (i) - 1 : (i)))

__global__ void __cluster_dims__(2, 1, 1) __launch_bounds__(NTHREADS, 1) fused_kernel(
    Scratch* __restrict__ sc,
    const __nv_bfloat16* __restrict__ x, const __nv_bfloat16* __restrict__ wqkv, const __nv_bfloat16* __restrict__ wo, const __nv_bfloat16* __restrict__ wr,
    const __nv_bfloat16* __restrict__ wd, __nv_bfloat16* __restrict__ out, const int by_sm, const __grid_constant__ Roles roles,
    const __grid_constant__ CUtensorMap tm_x, const __grid_constant__ CUtensorMap tm_w, const __grid_constant__ CUtensorMap tm_wt,
    const __grid_constant__ CUtensorMap tm_wo, const __grid_constant__ CUtensorMap tm_d,
    const __grid_constant__ CUtensorMap tm_g, const __grid_constant__ CUtensorMap tm_u, const __grid_constant__ CUtensorMap tm_o)
{
    extern __shared__ __align__(1024) unsigned char smem[];
    uint32_t sb, smid;
    asm volatile("mov.u32 %0, %1;" : "=r"(sb) : "r"(smem_u32(smem)));
    asm volatile("mov.u32 %0, %%smid;" : "=r"(smid));
    const uint32_t bid = blockIdx.x, tid = threadIdx.x;
    const unsigned cta = roles.pair[(by_sm ? smid : bid) >> 1] * 2 + (bid & 1);
    const int warp = __shfl_sync(0xffffffffu, tid >> 5, 0), lane = tid & 31;
    const uint32_t bars = sb + SM_BAR;
    if (warp == 8) {
        if (elect_one()) {
            mbar_init(bars + BAR_FULL * 8, 1); mbar_init(bars + BAR_F0B * 8, 1);
            asm volatile("fence.mbarrier_init.release.cluster;" ::: "memory");
        }
        __syncwarp();
    }
    if (warp == 9) {
        if (elect_one()) {
#pragma unroll
            for (int s = 1; s < NBAR; s++) if (s != BAR_F0B) mbar_init(bars + s * 8, (s >> 2) == 1 ? 4 : (s >= BAR_AE ? 4 : (s == BAR_PA ? 8 : (s == BAR_CS ? 3 : (s >= BAR_OE + 2 ? 2 : 1)))));
            asm volatile("fence.mbarrier_init.release.cluster;" ::: "memory");
        }
        __syncwarp();
    }
    cluster_arrive();
#define NPF 5
#define NPFX 2
    if (warp < NPF && bid < NCTA) {
        if (warp) __nanosleep(PF1_NS * warp);
        const char* qw = reinterpret_cast<const char*>(wqkv) + ((warp + (lane >= 15 ? KROT : 0)) * 1920 + bid * 15 + (lane >= 15 ? lane - 15 : lane)) * 128;
        const char* qx = lane < 16 ? reinterpret_cast<const char*>(x) + (bid * 16 + lane) * 1280 + (warp + ((bid >> 4) & 1) * KROT) * 128 : reinterpret_cast<const char*>(wr) + (lane - 16) * 128;
        if (lane < 30) asm volatile("prefetch.global.L2 [%0];" :: "l"(qw) : "memory");
        if (warp < NPFX && (lane < 16 || (bid == 0 && lane < 26))) asm volatile("prefetch.global.L2 [%0];" :: "l"(qx) : "memory");
    }
    if (cta >= NCTA) { cluster_wait(); service_cta(sc, x, sb, cta - NCTA, tid); return; }
    const int rank = cta & 1, g = (cta >> 1) & 7, G = cta >> 4, m = 2 * G + rank, odd = g & 1;
    const int k0 = (G & 1) * KROT * 64;
    const int cm = g * 80 + odd * 16, ct = g * 80 + 64 - odd * 64;

    if (warp == 8 && elect_one()) {
        const uint32_t st = sb + 2 * STAGE;
        mbar_expect_tx(bars + BAR_FULL * 8, OFF_B + B_HALF); mbar_expect_tx(bars + BAR_F0B * 8, B_HALF + 1280);
        tma3d(st, &tm_x, bars + BAR_FULL * 8, k0, m * 64, 0);
        tma3d(st + OFF_B, &tm_w, bars + BAR_FULL * 8, cm, k0, 0);
        tma3d(st + OFF_B + 12288, &tm_wt, bars + BAR_FULL * 8, ct, k0, 0);
        tma3d(st + OFF_B + B_HALF, &tm_w, bars + BAR_F0B * 8, cm, k0 + 32, 0);
        tma3d(st + OFF_B + B_HALF + 12288, &tm_wt, bars + BAR_F0B * 8, ct, k0 + 32, 0);
        bulk_load(sb + SM_XSEL, wr, 1280, bars + BAR_F0B * 8);
        TL(16);
    }
    __syncwarp();
    if (warp >= 8) {
        asm volatile("setmaxnreg.dec.sync.aligned.u32 64;");
        const int mi = g < 6 ? G * 6 + g : 46 + G;
        const bool moe = g < 6 || (g == 6 && G >= 2);
        if (warp == 8) {
            const CUtensorMap* tm_gu = rank ? &tm_u : &tm_g;
            cluster_wait();
#pragma unroll 1
            for (int kt = 1; kt < 13; kt++) {
                if (kt >= 4) { mbar_wait(bars + (BAR_AE + min(kt, 9) - 4) * 8, 0); mbar_wait(bars + (BAR_EMPTY + (kt & 3)) * 8, ((kt >> 2) - 1) & 1); }
                if (elect_one()) {
                    if (kt < 10) {
                        const uint32_t fb = bars + (BAR_FULL + (kt & 3)) * 8, st = sb + ((kt + 2) & 3) * STAGE;
                        const int kk = kt * 64 + (kt < 5 ? k0 : -k0);
                        mbar_expect_tx(fb, STAGE);
                        tma3d(st, &tm_x, fb, kk, m * 64, 0);
                        tma3d_mc(st + OFF_B + rank * B_HALF, &tm_w, fb, cm, kk + rank * 32, 0);
                        tma3d(st + OFF_B + 12288, &tm_wt, fb, ct, kk, 0);
                        tma3d(st + OFF_B + B_HALF + 12288, &tm_wt, fb, ct, kk + 32, 0);
                        if (kt == WOP) prefetch_l2_bulk(reinterpret_cast<const char*>(wo) + cta * 6400, 6400);
                        if (kt == 1) { mbar_expect_tx(bars + BAR_WO * 8, 81920); mbar_expect_tx(bars + BAR_GW * 8, 40960); mbar_expect_tx(bars + BAR_DW * 8, 20480); }
                    }
                    if (moe) {
                        if (kt >= 4 && kt < 12) { const int gp = kt < 9 ? kt - 2 : (kt < 11 ? kt - 9 : 7); tma2d(sb + (kt == 11 ? SM_G7 : SM_MW + gp * 5120), tm_gu, bars + BAR_GW * 8, mi * 32, gp * 80); }
                        if ((unsigned)(kt - DP0) < 2u) prefetch_l2_bulk(wd + (mi * 32 + rank * 16 + (kt - DP0) * 8) * DM, 10240);
                        if (kt == 12) {
#pragma unroll 1
                            for (int i = 0; i < 5; i++) tma2d(sb + SM_DW + i * 4096, &tm_d, bars + BAR_DW * 8, (rank * 5 + i) * 64, mi * 32);
                        }
                    }
                    if ((kt & ~1) == 10) {
#pragma unroll 1
                        for (int i = (kt - 10) * 4 + rank; i < (kt - 9) * 4; i += 2) tma2d_mc(sb + SM_WO + i * 10240, &tm_wo, bars + BAR_WO * 8, cm, SRC(i) * 80);
                    }
                    if (kt == 3) TL(17);
                }
                __syncwarp();
            }
            {
                const int r = lane >> 1;
#pragma unroll 1
                for (int i = 0; i < 8; i++) {
                    const __nv_bfloat16* src = wo + (SRC(i) * 80 + r) * DM + ct + (lane & 1) * 8;
                    const uint32_t dst = sb + SM_WT + (i & 1) * 10240 + r * 128 + ((((i & 6) + (lane & 1)) ^ (r & 7)) << 4);
#pragma unroll
                    for (int t = 0; t < 5; t++) cp_async16(dst + t * 2048, src + t * 16 * DM);
                }
                asm volatile("cp.async.wait_all;\nfence.proxy.async.shared::cta;" ::: "memory");
                __syncwarp();
                if (lane == 0) { mbar_arrive(bars + BAR_WO * 8); TL(19); }
            }
            const uint4* os = &sc->o[m][0][0][0];
            const uint4* fl = reinterpret_cast<const uint4*>(&sc->flag[m][0][0]) + (lane & 15);
            mbar_wait(bars + (BAR_EMPTY + 1) * 8, 0);
            mbar_wait(bars + BAR_PA * 8, 0);
            unsigned lvl = 0, spins = 0;
#pragma unroll 1
            for (int t = 0; t < 5; t++) {
                while (lvl <= t) {
                    const uint4 f = ld_relaxed_v4(fl);
                    lvl = __reduce_min_sync(0xffffffffu, min(min(f.x, f.y), min(f.z, f.w)));
                    spin_guard(spins);
                }
                if (t) mbar_wait(bars + (BAR_OE + t - 1) * 8, 0);
                if (elect_one()) {
                    const uint32_t dst = sb + (t == 2 ? SM_O2 : ((t == 0 || t == 3) ? SM_O0 : SM_O1)), fb = bars + (BAR_OF + t) * 8;
                    mbar_expect_tx(fb, 28672);
                    if (g > 0) bulk_load(dst, os + t * 2048, g * 4096, fb);
                    if (g < 7) bulk_load(dst + g * 4096, os + t * 2048 + (g + 1) * 256, (7 - g) * 4096, fb);
                    TL(48 + t);
                }
                __syncwarp();
            }
        } else {
            const int ta = tid - 288, wa = warp - 9, c = lane & 3, r = lane >> 2;
            const unsigned tag = ld_relaxed_u32(&sc->epoch[cta * 32]) + 1;
            const Outbox* const box = &sc->box[g >> 1];
            unsigned spins = 0;
            if (wa == 0) {
                uint4 *ro = &sc->o[m][0][g][lane], *rh = &sc->halo[m * 8 + g][lane];
                if (lane < 2) st_relaxed_v4(&sc->rdone[m * 8 + g][lane * 4], make_uint4(0, 0, 0, 0));
                cluster_wait();
                if (lane == 0) mbar_expect_tx(bars + BAR_PX * 8, 256);
#pragma unroll 1
                for (int t = 0; t < 5; t++, ro += 2048, rh += 64) {
                    mbar_wait(bars + (BAR_AE + RS_PACE(t)) * 8, 0);
                    const uint4 e = make_uint4(EMPTY_WORD, EMPTY_WORD, EMPTY_WORD, EMPTY_WORD);
#pragma unroll
                    for (int i = 0; i < 8; i++) st_relaxed_v4(ro + 32 * i, e);
                    st_relaxed_v4(rh, e); st_relaxed_v4(rh + 32, e);
                }
                if (lane < 2) st_relaxed_v4(&sc->flag[m][g][lane * 4], make_uint4(0, 0, 0, 0));
                fence_gpu();
                __syncwarp();
                if (lane == 0) { st_relaxed_u32(&sc->rdone[m * 8 + g][0], tag); TL(20); }
                const unsigned* rd = lane < 8 ? &sc->rdone[m * 8 + lane][0] : (lane == 8 && m > 0 ? &sc->rdone[m * 8 + g - 8][0] : &sc->open[g >> 1][0]);
                while (!__all_sync(0xffffffffu, ld_relaxed_u32(rd) == tag)) { __nanosleep(POLL_NS); spin_guard(spins); }
                if (lane == 0) { mbar_arrive(bars + BAR_RS * 8); TL(21); }
                while (ld_relaxed_u32(&box->msg[80]) == EMPTY_WORD) { __nanosleep(POLL_NS); spin_guard(spins); }
                uint4 q[6];
                while (true) {
#pragma unroll
                    for (int j = 0; j < 6; j++) q[j] = ld_relaxed_v4(&box->msg[min(lane + 32 * j, 160)]);
                    __syncwarp();
                    if (__all_sync(0xffffffffu, max(max(max(q[0].x, q[1].x), max(q[2].x, q[3].x)), max(q[4].x, q[5].x)) != EMPTY_WORD)) break;
                    spin_guard(spins);
                }
#pragma unroll
                for (int j = 0; j < 6; j++) sts_v4(sb + SM_XSEL + min(lane + 32 * j, 160) * 16, q[j]);
                __syncwarp();
                if (lane == 0) { mbar_arrive(bars + BAR_SEL * 8); TL(23); }
            } else {
                const bool cw = wa < 3, aside = wa >= 5;
                const int l = min(lane, 29), part = l < 24 ? l >> 3 : (l - 24) >> 1;
                const int pp = warp & 1, ri = lane >> 3;
                const uint32_t side = SM_MW + pp * 4096 + lane * 16;
                uint32_t ad[4];
#pragma unroll
                for (int i = 0; i < 4; i++) {
                    const int row = 4 * ((G & 6) + pp) + i;
                    ad[i] = cw ? OFF_B + rank * B_HALF + (l < 24 ? part * 4096 + row * 128 + (((l ^ row) & 7) << 4) : 12288 + part * 1024 + row * 32 + (((l ^ pp) & 1) << 4))
                               : pp * 8192 + (8 * g + ri + 4 * i) * 128 + (((lane ^ (ri + 4 * i)) & 7) << 4);
                    if (aside) ad[i] = side + i * 2048;
                    if (!cw && i == 2) ad[i] = SM_XSEL + (lane & 7) * 16 + (aside ? 768 - 2 * k0 : 2 * k0);
                    ad[i] = __shfl_sync(0xffffffffu, sb + ad[i], lane);
                }
                float s[8];
#pragma unroll
                for (int e = 0; e < 8; e++) s[e] = 0.f;
                if (wa == 2) {
#pragma unroll 1
                    for (int i = lane; i < 140; i += 32) sts_v4(sb + SM_BX + i * 16, make_uint4(0, 0, 0, 0));
                }
                cluster_wait();
                mbar_wait(bars + BAR_F0B * 8, 0);
                if (aside) {
                    const __nv_bfloat16* p0 = x + (m * 128 + g * 16 + 2 * ri + pp) * DM + 384 - k0 + (lane & 7) * 8;
                    mbar_wait(bars + (BAR_AE + SIDE_N) * 8, 0);
#pragma unroll 1
                    for (int j = 0; j < 4; j++) { cp_async16(sb + side + j * 512, p0 + j * 64); cp_async16(sb + side + 2048 + j * 512, p0 + 8 * DM + j * 64); }
                    asm volatile("cp.async.wait_all;" ::: "memory");
                }
#pragma unroll 1
                for (int kt = 0; kt < (cw ? 5 : (aside ? 4 : 6)); kt++) {
                    const uint32_t so = aside ? kt * 512 : ((kt + 2) & 3) * STAGE;
                    if (!aside) mbar_wait(bars + (BAR_FULL + (kt & 3)) * 8, kt >> 2);
                    const uint4 v0 = lds_v4(ad[0] + so), v1 = lds_v4(ad[1] + so), v2 = lds_v4(ad[2] + (cw ? so : kt * 128 - (kt == 5 ? 4 * k0 : 0)));
                    if (cw) {
                        const uint4 v3 = lds_v4(ad[3] + so);
#pragma unroll
                        for (int e = 0; e < 4; e++) {
                            s[2 * e] += (bf_lo((&v0.x)[e]) + bf_lo((&v1.x)[e])) + (bf_lo((&v2.x)[e]) + bf_lo((&v3.x)[e]));
                            s[2 * e + 1] += (bf_hi((&v0.x)[e]) + bf_hi((&v1.x)[e])) + (bf_hi((&v2.x)[e]) + bf_hi((&v3.x)[e]));
                        }
                    } else {
#pragma unroll
                        for (int e = 0; e < 4; e++) {
                            const float wl = bf_lo((&v2.x)[e]), wh = bf_hi((&v2.x)[e]);
                            const float a = bf_lo((&v0.x)[e]), b = bf_hi((&v0.x)[e]), a2 = bf_lo((&v1.x)[e]), b2 = bf_hi((&v1.x)[e]);
                            s[0] += a + b; s[1] = fmaf(b, b, fmaf(a, a, s[1])); s[2] = fmaf(b, wh, fmaf(a, wl, s[2])); s[3] += wl;
                            s[4] += a2 + b2; s[5] = fmaf(b2, b2, fmaf(a2, a2, s[5])); s[6] = fmaf(b2, wh, fmaf(a2, wl, s[6])); s[7] += wh;
                        }
                    }
                    __syncwarp();
                    if ((!aside || kt == 3) && lane == 0) mbar_arrive(bars + (BAR_AE + (aside ? 5 : kt)) * 8);
                }
                if (cw) {
                    uint4* const dst = &sc->cs[g][2 * m + pp][2 * lane];
                    st_relaxed_v4(dst, make_uint4(tagf(s[0], tag), __float_as_uint(s[1]), __float_as_uint(s[2]), __float_as_uint(s[3])));
                    st_relaxed_v4(dst + 1, make_uint4(tagf(s[4], tag), __float_as_uint(s[5]), __float_as_uint(s[6]), __float_as_uint(s[7])));
                    if (wa == 1 && lane == 0) TL(18);
                    if (wa == 2) {
                        while (ld_relaxed_u32(&sc->open[g >> 1][0]) != tag) spin_guard(spins);
                        uint4 b[3];
                        while (true) {
                            __nanosleep(POLL_NS);
#pragma unroll
                            for (int j = 0; j < 3; j++) b[j] = ld_relaxed_v4(&box->bx[g & 1][j][l]);
                            if (__all_sync(0xffffffffu, max(max(b[0].x, b[1].x), b[2].x) != EMPTY_WORD)) break;
                            spin_guard(spins);
                        }
#pragma unroll
                        for (int j = 0; j < 3; j++) {
                            const int row = 3 * part + j;
                            sts_v4(sb + SM_BX + (l < 24 ? row * 128 + (((l ^ row) & 7) << 4) : 1792 + row * 32 + (((l ^ (row >> 2)) & 1) << 4)), b[j]);
                        }
                        asm volatile("fence.proxy.async.shared::cta;" ::: "memory");
                        __syncwarp();
                        if (lane == 0) { mbar_arrive(bars + BAR_CS * 8); TL(25); }
                    }
                } else {
                    s[3] += s[7]; s[7] = s[3];
#pragma unroll
                    for (int e = 0; e < 4; e++) s[e] = ((lane & 4) ? s[4 + e] : s[e]) + shfl_x((lane & 4) ? s[e] : s[4 + e], 4);
#pragma unroll
                    for (int o = 1; o < 4; o <<= 1) {
#pragma unroll
                        for (int e = 0; e < 4; e++) s[e] += shfl_x(s[e], o);
                    }
                    const uint32_t sa = sb + SM_GT + pp * 128 + r * 16;
                    if (!aside) { sts_f4(sa, s[0], s[1], s[2], s[3]); asm volatile("bar.arrive 6, 128;" ::: "memory"); }
                    else {
                        bar_sync<6, 128>();
                        const float4 o = lds_f4(sa);
                        const int row = 8 * g + ri + (lane & 4);
                        const float mean = (s[0] + o.x) * (1.0f / DM), mb = bfr(mean);
                        const float sd = bfr(sqrt_approx(bfr(bfr(fmaxf(fmaf(-mean, mean, (s[1] + o.y) * (1.0f / DM)), 0.f)) + 1e-5f)));
                        const uint32_t u = __float_as_uint(bfr(fmaf(-mb, s[3] + o.w, s[2] + o.z) * rcp(sd))) >> 16;
                        if (c == 0)
                            st_relaxed_v2(&sc->rowinfo[m][pp][row], (__float_as_uint(mb) >> 16) | (__float_as_uint(sd) & 0xffff0000u),
                                          (((u & 0x8000u) ? (u ^ 0xffffu) : (u | 0x8000u)) << 16) | ((2047 - (m * 128 + 2 * row + pp)) << 5) | (tag & 31));
                        if (tid == 448) TL(22);
                    }
                    if (aside) {
                        const uint4* r0 = reinterpret_cast<const uint4*>(&sc->rowinfo[m][pp][0]);
                        uint4 a, b;
                        while (true) {
                            __nanosleep(POLL_NS);
                            a = ld_relaxed_v4(r0 + lane); b = ld_relaxed_v4(r0 + (m > 0 ? 28 - 64 : 0) + c);
                            if (__all_sync(0xffffffffu, (((a.y ^ tag) | (a.w ^ tag) | (b.y ^ tag) | (b.w ^ tag)) & 31) == 0)) break;
                            spin_guard(spins);
                        }
                        sts_f4(sb + SM_ST + (pp * 72 + 8 + 2 * lane) * 8, bf_lo(a.x), rcp(bf_hi(a.x)), bf_lo(a.z), rcp(bf_hi(a.z)));
                        if (lane < 4) sts_f4(sb + SM_ST + (pp * 72 + 2 * lane) * 8, bf_lo(b.x), rcp(bf_hi(b.x)), bf_lo(b.z), rcp(bf_hi(b.z)));
                        __syncwarp();
                        if (lane == 0) { mbar_arrive(bars + BAR_CS * 8); if (pp == 0) TL(24); }
                    }
                }
            }
            bar_sync<3, NAUX>();
            if (moe) {
                const int krow = (lane >> 4) * 8 + (lane & 7), ch = (lane >> 3) & 1;
                const uint32_t wofs = krow * 64 + ((ch ^ (krow >> 1)) & 3) * 16, xa = sb + SM_XSEL + (lane & 1) * 1296 + ch * 16;
                float d[2][4];
#pragma unroll
                for (int e = 0; e < 8; e++) d[e >> 2][e & 3] = 0.f;
                mbar_wait(bars + BAR_GW * 8, 0);
                mbar_wait(bars + (BAR_EMPTY + 1) * 8, 0);
                if (ta == 0) TL(26);
#pragma unroll 1
                for (int ks = wa; ks < 40; ks += 21) {
                    uint32_t a[6][4], b[3][2];
#pragma unroll
                    for (int h = 0; h < 3; h++) {
                        const int k2 = min(ks + 7 * h, 39);
                        const uint32_t wp = sb + (k2 < 35 ? SM_MW : SM_G7 - 35 * 1024) + k2 * 1024 + wofs;
                        ldsm4t(wp, a[2 * h]); ldsm4t(wp ^ 32, a[2 * h + 1]); ldsm2(xa + k2 * 32, b[h][0], b[h][1]);
                    }
                    if (ks + 14 > 39) b[2][0] = b[2][1] = 0;
#pragma unroll
                    for (int e = 0; e < 6; e++) mma16(d[e & 1], a[e][0], a[e][1], a[e][2], a[e][3], b[e >> 1][0], b[e >> 1][1]);
                }
                if (c == 0) {
#pragma unroll
                    for (int e = 0; e < 4; e++) sts_f2(sb + SM_BX + wa * 256 + (e * 8 + r) * 8, d[e >> 1][2 * (e & 1)], d[e >> 1][2 * (e & 1) + 1]);
                }
                bar_sync<3, NAUX>();
                if (ta == 64) { mbar_arrive(bars + BAR_OE * 8); TL(27); }
                if (wa < 2) {
                    float sum = 0.f;
#pragma unroll
                    for (int e = 0; e < 7; e++) sum += lds_f32(sb + SM_BX + e * 256 + ta * 4);
                    sum = bfr(sum);
                    st_async_peer(sb + SM_GU + ta * 4, bars + BAR_PX * 8, rank ^ 1, __float_as_uint(sum));
                    mbar_wait(bars + BAR_PX * 8, 0);
                    const float oth = lds_f32(sb + SM_GU + ta * 4), gs = rank ? oth : sum, us = rank ? sum : oth;
                    sts_u16(sb + SM_H + (ta & 1) * 64 + (ta >> 1) * 2, pack_bf16(bfr(gs * sigmoid_f(gs)) * us, 0.f));
                }
                mbar_wait(bars + BAR_DW * 8, 0);
                bar_sync<3, NAUX>();
                if (wa >= 3) {
                    uint32_t hb[4];
                    ldsm4(sb + SM_H + (lane & 1) * 64 + (lane >> 3) * 16, hb[0], hb[1], hb[2], hb[3]);
                    float yv[5];
#pragma unroll
                    for (int b = 0; b < 5; b++) {
                        const int nb = (wa - 3) * 5 + b;
                        const uint32_t wp = sb + SM_DW + (nb >> 2) * 4096 + krow * 128 + ((((nb & 3) * 2 + ch) ^ (krow & 7)) << 4);
                        uint32_t a0[4], a1[4];
                        ldsm4t(wp, a0); ldsm4t(wp + 2048, a1);
                        float o[4] = {0.f, 0.f, 0.f, 0.f};
                        mma16(o, a0[0], a0[1], a0[2], a0[3], hb[0], hb[1]); mma16(o, a1[0], a1[1], a1[2], a1[3], hb[2], hb[3]);
                        yv[b] = (c & 2) ? ((c & 1) ? o[3] : o[2]) : ((c & 1) ? o[1] : o[0]);
                    }
                    uint4* const dst = &sc->yp[rank * 4 + wa - 3][mi][0];
                    st_relaxed_v4(dst + lane, make_uint4(tagf(yv[0], tag), __float_as_uint(yv[1]), __float_as_uint(yv[2]), __float_as_uint(yv[3])));
                    st_relaxed_u32(reinterpret_cast<unsigned*>(dst + 32) + lane, tagf(yv[4], tag));
                    bar_sync<7, 128>();
                    if (tid == 384) { mbar_arrive(bars + (BAR_OE + 1) * 8); TL(28); }
                }
            } else if (ta == 0) { mbar_arrive(bars + BAR_OE * 8); mbar_arrive(bars + (BAR_OE + 1) * 8); }
            if (wa == 2) {
                const uint2 sel = lds_v2(sb + SM_TOP);
                if ((sel.x >> 7) == m || (sel.y >> 7) == m) {
                    uint4 v;
                    do { __nanosleep(POLL_NS); v = ld_relaxed_v4(&box->gt[g & 1][min(lane, 19)]); spin_guard(spins); } while (__any_sync(0xffffffffu, v.x == EMPTY_WORD));
                    sts_v4(sb + SM_GT + min(lane, 19) * 16, v);
                    __syncwarp();
                    if (lane == 0) TL(30);
                }
                if (lane == 0) { mbar_arrive(bars + BAR_Y * 8); st_relaxed_u32(&sc->epoch[cta * 32], tag); }
            }
        }
    } else {
        asm volatile("setmaxnreg.inc.sync.aligned.u32 192;");
        const int p = warp >> 2, w = warp & 3, c = lane & 3, r = lane >> 2;
        const uint32_t stb = sb + SM_ST + (p * 72 + w * 16) * 8;
        float acc[120];
#pragma unroll
        for (int i = 0; i < 120; i++) asm volatile("" : "=f"(acc[i]));
        uint32_t xs[5][4];
#pragma unroll
        for (int i = 0; i < 20; i++) asm volatile("" : "=r"(xs[i >> 2][i & 3]));
        cluster_wait();
        {
            const int lr = w * 16 + (lane & 15);
            uint32_t st = __shfl_sync(0xffffffffu, sb + 2 * STAGE + p * 8192 + lr * 128 + (((lr & 7) ^ (lane >> 4)) << 4), lane);
            const bool lead = __shfl_sync(0xffffffffu, tid & 127, lane) == 0;
            uint32_t blo = (((sb + 2 * STAGE + OFF_B) & 0x3ffffu) >> 4) | ((4096u >> 4) << 16);
            const uint32_t tdiff = (12288u >> 4) + ((1024u >> 4) << 16) - ((4096u >> 4) << 16);
            const int kx = (5 * g) >> 2;
            uint32_t af[4][4];
            mbar_wait(bars + BAR_FULL * 8, 0);
            if (tid == 0) TL(32);
            ldsm4(st, af[0][0], af[0][1], af[0][2], af[0][3]);
#pragma unroll 1
            for (int kt = 0; kt < 10; kt++) {
#pragma unroll
                for (int j = 0; j < 4; j++) {
                    uint32_t (&nx)[4] = af[(j + 1) & 3];
                    if (j == 2 && kt == 0) mbar_wait(bars + BAR_F0B * 8, 0);
                    if (j == 3 && kt < 9) {
                        st += (kt & 3) == 1 ? -3 * STAGE : STAGE;
                        mbar_wait(bars + (BAR_FULL + ((kt + 1) & 3)) * 8, ((kt + 1) >> 2) & 1);
                    }
                    ldsm4(st ^ (((j + 1) & 3) << 5), nx[0], nx[1], nx[2], nx[3]);
                    wg_fence();
                    const uint32_t sd = j ? 1u : (uint32_t)kt;
                    wgmma_rs_n48(acc, af[j][0], af[j][1], af[j][2], af[j][3], blo + tdiff + (j >> 1) * (B_HALF >> 4) + (j & 1) * 32, sd);
                    wgmma_rs_n192(acc, af[j][0], af[j][1], af[j][2], af[j][3], blo + (j >> 1) * (B_HALF >> 4) + (j & 1) * 128, sd);
                    wg_commit();
                    wg_wait<1>();
                    if (j == 0 && kt > 0 && lead) mbar_arrive_both(bars + (BAR_EMPTY + ((kt - 1) & 3)) * 8);
                    const int kg = kt + ((kt < 5 ? k0 : -k0) >> 6);
                    if (j == 1 && (unsigned)(kg - kx) < 2u) {
#pragma unroll
                        for (int t = 0; t < 5; t++) {
                            const int ks = 5 * g + (t < 4 ? t + odd : 4 - 4 * odd);
                            ldsm4_if((ks >> 2) == kg, st ^ ((ks & 3) << 5), xs[t]);
                        }
                    }
                }
                blo += (kt & 3) == 1 ? -3 * (STAGE >> 4) : (STAGE >> 4);
            }
        }
        mbar_wait(bars + BAR_CS * 8, 0);
        if (tid == 0) TL(10);
        const float2 st0 = lds_f2(stb + (8 + r) * 8), st1 = lds_f2(stb + (16 + r) * 8);
        {
            const uint32_t msk = c == 0 ? 0xffffffffu : (c == 1 ? 0x0000ffffu : 0u);
            const uint32_t e0 = dup_hi(-st0.x) & msk, e1 = dup_hi(-st1.x) & msk;
            wg_fence();
            wgmma_rs_n48x(acc, e0, e1, 0u, 0u, (((sb + SM_BX + 1792) & 0x3ffffu) >> 4) | ((96u >> 4) << 16));
            wgmma_rs_n192x(acc, e0, e1, 0u, 0u, (((sb + SM_BX) & 0x3ffffu) >> 4) | ((384u >> 4) << 16));
            wg_commit();
        }
        const float rs0 = st0.y, rs1 = st1.y;
        const uint4 sP = lds_v4(stb + (2 * c) * 8), sB = lds_v4(stb + (8 + 2 * c) * 8), sC = lds_v4(stb + (16 + 2 * c) * 8);
        const bool up0 = 2 * c > r, up1 = 2 * c + 1 > r;
        const float k00 = __uint_as_float(up0 ? sP.y : sB.y), k01 = __uint_as_float(up1 ? sP.w : sB.w);
        const float k10 = __uint_as_float(up0 ? sB.y : sC.y), k11 = __uint_as_float(up1 ? sB.w : sC.w);
        const float sc2 = 0.22360679774997896f * 1.4426950408889634f;
        const float f00 = rs0 * k00 * sc2, f01 = rs0 * k01 * sc2, f10 = rs1 * k10 * sc2, f11 = rs1 * k11 * sc2;
        const bool first = (m == 0 && w == 0);
        const float b00 = (first && up0) ? -1e30f : 0.f, b01 = (first && up1) ? -1e30f : 0.f;
        const uint32_t mup = (up0 ? 0x0000ffffu : 0u) | (up1 ? 0xffff0000u : 0u);
        uint4* const exs = reinterpret_cast<uint4*>(smem + SM_EX) + p * 512 + lane;
        uint4* hdst = w == 3 ? &sc->halo[m * 8 + g][p * 160 + lane] : exs + w * 160;
        const uint4* hsrc = w > 0 ? exs + (w - 1) * 160 : (m > 0 ? &sc->halo[m * 8 + g - 8][p * 160 + lane] : exs);
        uint32_t* ob = reinterpret_cast<uint32_t*>(&sc->o[m][0][g][warp * 32]) + lane;
        unsigned* of_ = &sc->flag[m][g][warp];
        asm volatile("" : "+l"(hdst), "+l"(hsrc), "+l"(ob), "+l"(of_));
        mbar_wait(bars + BAR_RS * 8, 0);
        if (p == 0) bar_sync<1, 128>(); else bar_sync<2, 128>();
        wg_wait<0>();
        if ((tid & 127) == 0) { mbar_arrive_both(bars + (BAR_EMPTY + 1) * 8); TL(2 + p); }
        uint32_t Q[10][2], K[10][2], V[10][2], Kp[10], Vp[10];
        if (odd) pack_kv<1, 1>(acc, K, V); else pack_kv<0, 1>(acc, K, V);
        st_gen_v4(hdst, make_uint4(K[0][1], K[1][1], K[2][1], K[3][1])); st_gen_v4(hdst + 32, make_uint4(K[4][1], K[5][1], K[6][1], K[7][1]));
        st_gen_v4(hdst + 64, make_uint4(K[8][1], K[9][1], V[0][1], V[1][1])); st_gen_v4(hdst + 96, make_uint4(V[2][1], V[3][1], V[4][1], V[5][1]));
        st_gen_v4(hdst + 128, make_uint4(V[6][1], V[7][1], V[8][1], V[9][1]));
        if (tid == 96) TL(11);
        if (odd) { pack_kv<1, 0>(acc, K, V); pack_q<1>(acc, Q); } else { pack_kv<0, 0>(acc, K, V); pack_q<0>(acc, Q); }
        {
            if (p == 0) bar_sync<1, 128>(); else bar_sync<2, 128>();
            uint4 rcv[5];
            unsigned spins = 0;
            while (true) {
#pragma unroll
                for (int i = 0; i < 5; i++) rcv[i] = ld_gen_v4(hsrc + i * 32);
                const unsigned mx = max(max(max(rcv[0].x, rcv[1].x), max(rcv[2].x, rcv[3].x)), rcv[4].x);
                if (__all_sync(0xffffffffu, mx != EMPTY_WORD) || ++spins > SPIN_MAX) break;
            }
            Kp[0] = rcv[0].x; Kp[1] = rcv[0].y; Kp[2] = rcv[0].z; Kp[3] = rcv[0].w; Kp[4] = rcv[1].x; Kp[5] = rcv[1].y; Kp[6] = rcv[1].z; Kp[7] = rcv[1].w;
            Kp[8] = rcv[2].x; Kp[9] = rcv[2].y; Vp[0] = rcv[2].z; Vp[1] = rcv[2].w; Vp[2] = rcv[3].x; Vp[3] = rcv[3].y; Vp[4] = rcv[3].z; Vp[5] = rcv[3].w;
            Vp[6] = rcv[4].x; Vp[7] = rcv[4].y; Vp[8] = rcv[4].z; Vp[9] = rcv[4].w;
        }
        if (tid == 0) TL(4);
        if (tid == 32) TL(5);
        uint32_t of[10][2];
#define PUBLISH(t) do { st_relaxed_u32(ob + (t) * 8192, of[2 * (t)][0]); st_relaxed_u32(ob + (t) * 8192 + 32, of[2 * (t) + 1][0]); \
            st_relaxed_u32(ob + (t) * 8192 + 64, of[2 * (t)][1]); st_relaxed_u32(ob + (t) * 8192 + 96, of[2 * (t) + 1][1]); \
            if (lane == 0) st_relaxed_u32(of_, (t) + 1); } while (0)
#pragma unroll
        for (int hp = 0; hp < 2; hp++) {
            float sp[2][4], sm_[2][4], sn[2][4], O[5][4];
            const int bz = 5 * hp + 2;
#pragma unroll
            for (int b = 0; b < 5; b++) { O[b][0] = O[b][1] = O[b][2] = O[b][3] = 0.f; }
#pragma unroll
            for (int h = 0; h < 2; h++) {
                const int bx = 5 * hp + 3 * h, by = bx + 1;
                const bool qmine = h ? (c >= 2) : (c < 2);
                const uint32_t qz0 = qmine ? Q[bz][0] : 0u, qz1 = qmine ? Q[bz][1] : 0u;
#pragma unroll
                for (int e = 0; e < 4; e++) { sp[h][e] = 0.f; sm_[h][e] = 0.f; sn[h][e] = 0.f; }
                mma16(sm_[h], Q[bx][0], Q[bx][1], Q[by][0], Q[by][1], K[bx][0], K[by][0]);
                mma16(sn[h], Q[bx][0], Q[bx][1], Q[by][0], Q[by][1], K[bx][1], K[by][1]);
                mma16(sp[h], Q[bx][0], Q[bx][1], Q[by][0], Q[by][1], Kp[bx], Kp[by]);
                mma8(sm_[h], qz0, qz1, K[bz][0]); mma8(sn[h], qz0, qz1, K[bz][1]); mma8(sp[h], qz0, qz1, Kp[bz]);
            }
            float l[2][4], mx[2][2];
#pragma unroll
            for (int h = 0; h < 2; h++) {
                l[h][0] = fmaf(up0 ? sp[h][0] : sm_[h][0], f00, b00); l[h][1] = fmaf(up1 ? sp[h][1] : sm_[h][1], f01, b01);
                l[h][2] = (up0 ? sm_[h][2] : sn[h][2]) * f10; l[h][3] = (up1 ? sm_[h][3] : sn[h][3]) * f11;
                mx[h][0] = fmaxf(l[h][0], l[h][1]); mx[h][1] = fmaxf(l[h][2], l[h][3]);
            }
#pragma unroll
            for (int o = 1; o < 4; o <<= 1) {
#pragma unroll
                for (int h = 0; h < 2; h++) { mx[h][0] = fmaxf(mx[h][0], shfl_x(mx[h][0], o)); mx[h][1] = fmaxf(mx[h][1], shfl_x(mx[h][1], o)); }
            }
            float sum[2][2];
#pragma unroll
            for (int h = 0; h < 2; h++) {
                l[h][0] = ex2(l[h][0] - mx[h][0]); l[h][1] = ex2(l[h][1] - mx[h][0]); l[h][2] = ex2(l[h][2] - mx[h][1]); l[h][3] = ex2(l[h][3] - mx[h][1]);
                sum[h][0] = l[h][0] + l[h][1]; sum[h][1] = l[h][2] + l[h][3];
            }
#pragma unroll
            for (int o = 1; o < 4; o <<= 1) {
#pragma unroll
                for (int h = 0; h < 2; h++) { sum[h][0] += shfl_x(sum[h][0], o); sum[h][1] += shfl_x(sum[h][1], o); }
            }
#pragma unroll
            for (int h = 0; h < 2; h++) {
                const int bx = 5 * hp + 3 * h, by = bx + 1;
                const float i0 = rcp(sum[h][0]), i1 = rcp(sum[h][1]);
                const uint32_t pl = pack_bf16(l[h][0] * k00 * i0, l[h][1] * k01 * i0), ph = pack_bf16(l[h][2] * k10 * i1, l[h][3] * k11 * i1);
                const uint32_t a0 = pl & mup, a2 = pl & ~mup, a3 = ph & mup, c1 = ph & ~mup;
                const bool vmine = h ? (r >= 4) : (r < 4);
                mma16(O[3 * h], a0, 0u, a2, a3, Vp[bx], V[bx][0]);
                mma16(O[3 * h + 1], a0, 0u, a2, a3, Vp[by], V[by][0]);
                mma16(O[2], a0, 0u, a2, a3, vmine ? Vp[bz] : 0u, vmine ? V[bz][0] : 0u);
                mma8(O[3 * h], 0u, c1, V[bx][1]); mma8(O[3 * h + 1], 0u, c1, V[by][1]); mma8(O[2], 0u, c1, vmine ? V[bz][1] : 0u);
            }
#pragma unroll
            for (int b = 0; b < 5; b++) { of[5 * hp + b][0] = pack_bf16(O[b][0], O[b][1]); of[5 * hp + b][1] = pack_bf16(O[b][2], O[b][3]); }
            if (hp == 0) { PUBLISH(0); PUBLISH(1); if (lane == 0) mbar_arrive(bars + BAR_PA * 8); }
            if (tid == 0) TL(6 + hp);
            if (tid == 32) TL(8 + hp);
        }
#define TRK 0
        float acc2[40];
#pragma unroll
        for (int i = 0; i < 40; i++) asm volatile("" : "=f"(acc2[i]));
        uint32_t gate[5][4];
        PUBLISH(2);
        if (TRK == 0) { PUBLISH(3); PUBLISH(4); }
        const float rh0 = bfr(0.5f * rs0), rh1 = bfr(0.5f * rs1);
        const uint32_t gm[2] = {dup_hi(st0.x), dup_hi(st1.x)}, gh[2] = {dup_hi(rh0), dup_hi(rh1)};
        const uint32_t gl[2] = {pack_bf16(0.5f * rs0 - rh0, 0.5f * rs0 - rh0), pack_bf16(0.5f * rs1 - rh1, 0.5f * rs1 - rh1)};
        mbar_wait(bars + BAR_WO * 8, 0);
        bar_sync<4, 256>();
        if (tid == 0) TL(13);
        const uint32_t wlo = ((sb + SM_WO) & 0x3ffffu) >> 4, alo = (((sb + p * 2048) & 0x3ffffu) >> 4) | (8u << 16);
#define WDESC(ks) (wlo + (ks) * 128 + (((SM_WT - SM_WO + ((ks) % 10 - (ks)) * 2048 + ((ks) / 10) * 32) >> 4) << 16))
        wg_fence();
#pragma unroll
        for (int t = 0; t < 5; t++) wgmma_rs_n80(acc2, of[2 * t][0], of[2 * t][1], of[2 * t + 1][0], of[2 * t + 1][1], WDESC(t), t != 0);
        wg_commit();
#pragma unroll
        for (int t = 0; t < 5; t++) {
#pragma unroll
            for (int e = 0; e < 4; e++) {
                const uint32_t d = hsub2(xs[t][e], gm[e & 1]), h2 = hfma2(d, gh[e & 1], hmul2(d, gl[e & 1]));
                const float a = bf_lo(h2), b = bf_hi(h2);
                gate[t][e] = pack_bf16(fmaf(a, tanh_f(a), a), fmaf(b, tanh_f(b), b));
                asm volatile("" : "+r"(gate[t][e]) :: "memory");
            }
            if (TRK == 1 && t == 1) PUBLISH(3);
            if (TRK == 2 && t == 4) PUBLISH(3);
            if (TRK >= 1 && t == 4) PUBLISH(4);
        }
        if (tid == 0) TL(12);
#pragma unroll 1
        for (int t = 0; t < 5; t++) {
            const uint32_t ad = alo + ((t == 2 ? SM_O2 : ((t == 0 || t == 3) ? SM_O0 : SM_O1)) >> 4);
            mbar_wait(bars + (BAR_OF + t) * 8, 0);
            if (STAG < 5 && t == STAG && p == 1) bar_sync<5, 256>();
            wg_fence();
#pragma unroll
            for (int i = 0; i < 7; i++) {
                wgmma_ss_n80(acc2, ad + i * 256, WDESC((i + 1) * 5) + t * 128);
                if (i == 0) {
                    wg_commit(); wg_wait<1>();
                    if ((unsigned)(t - 1) < 2u && (tid & 127) == 0) mbar_arrive(bars + (BAR_OE + t + 1) * 8);
                }
                if (STAG < 5 && i == 4 && t == 4 && p == 0) asm volatile("bar.arrive 5, 256;" ::: "memory");
            }
            wg_commit();
        }
        const int wrow = m * 128 + 32 * w + p;
        {
            mbar_wait(bars + BAR_SEL * 8, 0);
            const uint2 sel = lds_v2(sb + SM_TOP);
            const unsigned d0 = sel.x - wrow, d1 = sel.y - wrow;
            if ((d0 & ~30u) == 0 || (d1 & ~30u) == 0) {
                mbar_wait(bars + BAR_Y * 8, 0);
#pragma unroll
                for (int h = 0; h < 2; h++) {
                    const unsigned me = 2 * r + 16 * h;
                    if (d0 == me || d1 == me) {
#pragma unroll
                        for (int t = 0; t < 5; t++) {
                            const uint32_t a = sb + SM_GT + (d0 == me ? 0 : 160) + (t < 4 ? t + odd : 4 - 4 * odd) * 32 + c * 4;
                            gate[t][h] = lds_u32(a); gate[t][2 + h] = lds_u32(a + 16);
                        }
                    }
                }
                __syncwarp();
            }
        }
        const uint32_t ssb = sb + SM_OUT + warp * 2560;
        const uint32_t laddr = ssb + (lane & 15) * 160 + (lane >> 4) * 16;
        wg_wait<0>();
        if (tid == 0) TL(1);
        if (tid == 128) TL(14);
        if (__any_sync(0xffffffffu, acc2[0] != acc2[0] || acc2[2] != acc2[2])) {
#pragma unroll
            for (int i = 0; i < 40; i++) acc2[i] = 0.f;
            const int krow = lane & 15;
#pragma unroll 1
            for (int ks = 0; ks < 40; ks++) {
                const int i = ks / 5;
                const uint32_t* src = ob + (ks - 5 * i) * 8192 + (SRC(i) - g) * 1024;
                uint32_t a0, a1, a2, a3; unsigned spins = 0;
                do { a0 = ld_relaxed_u32(src); a2 = ld_relaxed_u32(src + 32); a1 = ld_relaxed_u32(src + 64); a3 = ld_relaxed_u32(src + 96); }
                while (__any_sync(0xffffffffu, max(max(a0, a1), max(a2, a3)) == EMPTY_WORD) && ++spins < SPIN_MAX);
#pragma unroll
                for (int nb = 0; nb < 5; nb++) {
                    uint32_t b[4];
                    ldsm4t(sb + (nb < 4 ? SM_WO + ks * 2048 : SM_WT + (ks % 10) * 2048) + krow * 128 + (((2 * (nb < 4 ? nb : ks / 10) + (lane >> 4)) ^ (krow & 7)) << 4), b);
                    mma16(*reinterpret_cast<float (*)[4]>(&acc2[8 * nb]), a0, a1, a2, a3, b[0], b[1]);
                    mma16(*reinterpret_cast<float (*)[4]>(&acc2[8 * nb + 4]), a0, a1, a2, a3, b[2], b[3]);
                }
            }
        }
#pragma unroll
        for (int t = 0; t < 5; t++) {
            uint32_t o[4];
#pragma unroll
            for (int e = 0; e < 4; e++) o[e] = hadd2(xs[t][e], hmul2(pack_bf16(acc2[8 * t + 2 * e], acc2[8 * t + 2 * e + 1]), gate[t][e]));
            stsm4(laddr + (t < 4 ? t + odd : 4 - 4 * odd) * 32, o[0], o[1], o[2], o[3]);
        }
        asm volatile("fence.proxy.async.shared::cta;" ::: "memory");
        __syncwarp();
        if (elect_one()) tma3d_store(&tm_o, ssb, g * 80, m * 64 + w * 16, p);
    }
}

typedef CUresult (*EncodeFn)(CUtensorMap*, CUtensorMapDataType, cuuint32_t, void*, const cuuint64_t*, const cuuint64_t*, const cuuint32_t*,
                             const cuuint32_t*, CUtensorMapInterleave, CUtensorMapSwizzle, CUtensorMapL2promotion, CUtensorMapFloatOOBfill);

static void encode(EncodeFn enc, CUtensorMap* tm, const void* ptr, int rank, uint64_t d0, uint64_t d1, uint64_t d2, uint64_t s1, uint64_t s2,
                   uint32_t b0, uint32_t b1, uint32_t b2, CUtensorMapSwizzle swz) {
    cuuint64_t dims[3] = {d0, d1, d2}, strides[2] = {s1, s2};
    cuuint32_t box[3] = {b0, b1, b2}, es[3] = {1, 1, 1};
    enc(tm, CU_TENSOR_MAP_DATA_TYPE_BFLOAT16, rank, const_cast<void*>(ptr), dims, strides, box, es, CU_TENSOR_MAP_INTERLEAVE_NONE, swz,
        CU_TENSOR_MAP_L2_PROMOTION_L2_128B, CU_TENSOR_MAP_FLOAT_OOB_FILL_NONE);
}

}

extern "C" void kernel_launch(void* const* d_in, const int* in_sizes, int n_in, void* d_out, int out_size) {
    using namespace fk;
    (void)in_sizes; (void)n_in; (void)out_size;
    const __nv_bfloat16* x = (const __nv_bfloat16*)d_in[0];
    const __nv_bfloat16* wqkv = (const __nv_bfloat16*)d_in[1];
    const __nv_bfloat16* wo = (const __nv_bfloat16*)d_in[2];
    const __nv_bfloat16* wr = (const __nv_bfloat16*)d_in[4];
    const __nv_bfloat16* wg = (const __nv_bfloat16*)d_in[5];
    const __nv_bfloat16* wu = (const __nv_bfloat16*)d_in[6];
    const __nv_bfloat16* wd = (const __nv_bfloat16*)d_in[7];
    static EncodeFn enc = nullptr;
    static Scratch* scratch = nullptr;
    static Roles roles; static int by_sm = 0;
    if (!enc) {
        void* fn = nullptr; cudaDriverEntryPointQueryResult qr;
        cudaGetDriverEntryPoint("cuTensorMapEncodeTiled", &fn, cudaEnableDefault, &qr);
        enc = (EncodeFn)fn;
        cudaFuncSetAttribute(fused_kernel, cudaFuncAttributeMaxDynamicSharedMemorySize, SM_TOTAL);
        cudaGetSymbolAddress((void**)&scratch, g_scratch);
        int dev = 0, nsm = 0;
        cudaGetDevice(&dev); cudaDeviceGetAttribute(&nsm, cudaDevAttrMultiProcessorCount, dev);
        by_sm = nsm == NCTA + NIDLE;
        for (int t = 0; t < 66; t++) roles.pair[t] = t < 32 ? (t & 7) * 8 + (t >> 3) : (t < 60 ? (1 + (t - 32) % 7) * 8 + 4 + (t - 32) / 7 : (t < 62 ? t + 4 : t - 58));
    }
    CUtensorMap tx, tw, twt, two, td, tg, tu, to;
    encode(enc, &tx, x, 3, 640, 1024, 2, 2560, 1280, 64, 64, 2, CU_TENSOR_MAP_SWIZZLE_128B);
    encode(enc, &tw, wqkv, 3, 640, 640, 3, 3840, 1280, 64, 32, 3, CU_TENSOR_MAP_SWIZZLE_128B);
    encode(enc, &twt, wqkv, 3, 640, 640, 3, 3840, 1280, 16, 32, 3, CU_TENSOR_MAP_SWIZZLE_32B);
    encode(enc, &two, wo, 2, 640, 640, 1, 1280, 0, 64, 80, 1, CU_TENSOR_MAP_SWIZZLE_128B);
    encode(enc, &td, wd, 2, 640, 1728, 1, 1280, 0, 64, 32, 1, CU_TENSOR_MAP_SWIZZLE_128B);
    encode(enc, &to, d_out, 3, 640, 1024, 2, 2560, 1280, 80, 16, 1, CU_TENSOR_MAP_SWIZZLE_NONE);
    encode(enc, &tg, wg, 2, 1728, 640, 1, 3456, 0, 32, 80, 1, CU_TENSOR_MAP_SWIZZLE_64B);
    encode(enc, &tu, wu, 2, 1728, 640, 1, 3456, 0, 32, 80, 1, CU_TENSOR_MAP_SWIZZLE_64B);
    fused_kernel<<<NCTA + NIDLE, NTHREADS, SM_TOTAL>>>(scratch, x, wqkv, wo, wr, wd, (__nv_bfloat16*)d_out, by_sm, roles, tx, tw, twt, two, td, tg, tu, to);
}
```

```cpp
#include <cuda_runtime.h>
#include <cuda_bf16.h>
#include <cuda.h>
#include <stdint.h>

#define DEVI __device__ __forceinline__

namespace fk {

constexpr int DM = 640;
constexpr int NCTA = 128, NIDLE = 4, NTHREADS = 512;
constexpr int NMOE = 54;
constexpr int STAGE = 47104;
constexpr int OFF_B = 16384, B_HALF = 15360;
constexpr int SM_DW = 0;
constexpr int SM_WO = 33792;
constexpr int SM_G7 = SM_WO + 81920;
constexpr int SM_WT = SM_G7 + 5120;
constexpr int SM_EX = 3 * STAGE;
constexpr int SM_O0 = 3 * STAGE + OFF_B, SM_O1 = 4 * STAGE, SM_O2 = SM_DW;
constexpr int SM_MW = 4 * STAGE;
constexpr int SM_BX = SM_MW + 35840;
constexpr int SM_XSEL = SM_BX + 2240;
constexpr int SM_ST = SM_XSEL + 2592;
constexpr int SM_GT = SM_ST + 1152;
constexpr int SM_GU = SM_GT + 320;
constexpr int SM_H = SM_GU + 256;
constexpr int SM_TOP = SM_XSEL + 1280;
constexpr int SM_BAR = SM_H + 128;
constexpr int SM_TL = SM_BAR + 352;
constexpr int SM_TOTAL = SM_TL;
static_assert(SM_TOTAL <= 232448 && SM_BAR % 8 == 0 && SM_XSEL % 16 == 0 && SM_ST % 16 == 0 && SM_GT % 16 == 0 && SM_BX % 1024 == 0 && SM_TOP % 16 == 0, "smem layout");
constexpr int BAR_FULL = 0, BAR_EMPTY = 4, BAR_WR = 8, BAR_Y = 9, BAR_GW = 10, BAR_DW = 11, BAR_PX = 12, BAR_RS = 13, BAR_SEL = 14, BAR_GI = 15, BAR_CX = 42,
              BAR_OF = 16  , BAR_OE = 21  , BAR_WO = 25, BAR_CS = 26, BAR_PA = 27  , BAR_AE = 32  , BAR_FA = 38  , NBAR = 43;
#define POLL_NS 100
#define PF1_NS 200
#define STAG 3
#define GP0 4
#define DP0 9
constexpr uint32_t EMPTY_WORD = 0xffffffffu;
struct Roles { unsigned short pair[NCTA / 2 + NIDLE / 2]; };
constexpr unsigned SPIN_MAX = 1u << 20;

struct Outbox {
    uint4 msg[192];
    uint4 gt[2][32];
};
struct Scratch {
    uint4 o[16][5][8][256];
    uint4 halo[NCTA][320];
    unsigned flag[16][8][8];
    Outbox box[NIDLE];
    uint4 cs[8][8][2][32];
    uint4 yp[8][56][40];
    uint2 rowinfo[16][2][64];
    unsigned rdone[NCTA][8];
    unsigned open[NIDLE][32];
    unsigned epoch[(NCTA + NIDLE) * 32];
};
__device__ Scratch g_scratch;
#define TL(i) do { } while (0)

DEVI uint32_t smem_u32(const void* p) { return (uint32_t)__cvta_generic_to_shared(p); }
DEVI void mbar_init(uint32_t bar, uint32_t cnt) { asm volatile("mbarrier.init.shared::cta.b64 [%0], %1;" :: "r"(bar), "r"(cnt)); }
DEVI void mbar_expect_tx(uint32_t bar, uint32_t bytes) { asm volatile("mbarrier.arrive.expect_tx.shared::cta.b64 _, [%0], %1;" :: "r"(bar), "r"(bytes) : "memory"); }
DEVI void mbar_arrive(uint32_t bar) { asm volatile("mbarrier.arrive.shared::cta.b64 _, [%0];" :: "r"(bar) : "memory"); }
DEVI uint32_t clk32() { uint32_t t; asm volatile("mov.u32 %0, %%clock;" : "=r"(t) :: "memory"); return t; }
DEVI void sched_fence() { asm volatile("pmevent 0;" ::: "memory"); }
DEVI bool mbar_try(uint32_t bar, uint32_t parity) {
    uint32_t ok;
    asm volatile("{\n.reg .pred p;\nmbarrier.try_wait.parity.shared::cta.b64 p, [%1], %2, 0x989680;\nselp.u32 %0, 1, 0, p;\n}" : "=r"(ok) : "r"(bar), "r"(parity) : "memory");
    return ok != 0;
}
DEVI void mbar_wait(uint32_t bar, uint32_t parity) {
    while (!mbar_try(bar, parity)) { }
}
DEVI bool elect_one() {
    uint32_t p;
    asm volatile("{\n.reg .pred P;\nelect.sync _|P, 0xffffffff;\nselp.u32 %0, 1, 0, P;\n}" : "=r"(p));
    return p != 0;
}
DEVI void tma3d(uint32_t dst, const CUtensorMap* tm, uint32_t bar, int c0, int c1, int c2) {
    asm volatile("cp.async.bulk.tensor.3d.shared::cluster.global.mbarrier::complete_tx::bytes [%0], [%1, {%3, %4, %5}], [%2];"
                 :: "r"(dst), "l"(tm), "r"(bar), "r"(c0), "r"(c1), "r"(c2) : "memory");
}
DEVI void tma3d_mc(uint32_t dst, const CUtensorMap* tm, uint32_t bar, int c0, int c1, int c2) {
    asm volatile("cp.async.bulk.tensor.3d.shared::cluster.global.mbarrier::complete_tx::bytes.multicast::cluster [%0], [%1, {%3, %4, %5}], [%2], %6;"
                 :: "r"(dst), "l"(tm), "r"(bar), "r"(c0), "r"(c1), "r"(c2), "h"((uint16_t)3) : "memory");
}
DEVI void tma2d(uint32_t dst, const CUtensorMap* tm, uint32_t bar, int c0, int c1) {
    asm volatile("cp.async.bulk.tensor.2d.shared::cluster.global.mbarrier::complete_tx::bytes [%0], [%1, {%3, %4}], [%2];"
                 :: "r"(dst), "l"(tm), "r"(bar), "r"(c0), "r"(c1) : "memory");
}
DEVI void tma2d_prefetch(const CUtensorMap* tm, int c0, int c1) {
    asm volatile("cp.async.bulk.prefetch.tensor.2d.L2.global [%0, {%1, %2}];" :: "l"(tm), "r"(c0), "r"(c1) : "memory");
}
DEVI void tma2d_mc(uint32_t dst, const CUtensorMap* tm, uint32_t bar, int c0, int c1) {
    asm volatile("cp.async.bulk.tensor.2d.shared::cluster.global.mbarrier::complete_tx::bytes.multicast::cluster [%0], [%1, {%3, %4}], [%2], %5;"
                 :: "r"(dst), "l"(tm), "r"(bar), "r"(c0), "r"(c1), "h"((uint16_t)3) : "memory");
}
DEVI void mbar_arrive_both(uint32_t bar) {
    asm volatile("{\n.reg .b32 ra;\nmapa.shared::cluster.u32 ra, %0, 0;\nmbarrier.arrive.shared::cluster.b64 _, [ra];\n"
                 "mapa.shared::cluster.u32 ra, %0, 1;\nmbarrier.arrive.shared::cluster.b64 _, [ra];\n}" :: "r"(bar) : "memory");
}
DEVI void st_async_peer(uint32_t addr, uint32_t bar, uint32_t peer, uint32_t v) {
    asm volatile("{\n.reg .b32 ra, rb;\nmapa.shared::cluster.u32 ra, %0, %2;\nmapa.shared::cluster.u32 rb, %1, %2;\n"
                 "st.async.weak.shared::cluster.mbarrier::complete_tx::bytes.b32 [ra], %3, [rb];\n}" :: "r"(addr), "r"(bar), "r"(peer), "r"(v) : "memory");
}
DEVI void st_async_v4(uint32_t addr, uint32_t bar, uint32_t cta, float a, float b, float c, float d) {
    asm volatile("{\n.reg .b32 ra, rb;\nmapa.shared::cluster.u32 ra, %0, %2;\nmapa.shared::cluster.u32 rb, %1, %2;\n"
                 "st.async.weak.shared::cluster.mbarrier::complete_tx::bytes.v4.f32 [ra], {%3,%4,%5,%6}, [rb];\n}" :: "r"(addr), "r"(bar), "r"(cta), "f"(a), "f"(b), "f"(c), "f"(d) : "memory");
}
DEVI void bulk_load(uint32_t dst, const void* src, uint32_t bytes, uint32_t bar) {
    asm volatile("cp.async.bulk.shared::cluster.global.mbarrier::complete_tx::bytes [%0], [%1], %2, [%3];" :: "r"(dst), "l"(src), "r"(bytes), "r"(bar) : "memory");
}
DEVI void cluster_arrive() { asm volatile("barrier.cluster.arrive.relaxed.aligned;" ::: "memory"); }
DEVI void cluster_wait() { asm volatile("barrier.cluster.wait.aligned;" ::: "memory"); }
DEVI void wg_fence() { asm volatile("wgmma.fence.sync.aligned;" ::: "memory"); }
DEVI void wg_commit() { asm volatile("wgmma.commit_group.sync.aligned;" ::: "memory"); }
template <int N> DEVI void wg_wait() { asm volatile("wgmma.wait_group.sync.aligned %0;" :: "n"(N) : "memory"); }
template <int ID, int N> DEVI void bar_sync() { asm volatile("bar.sync %0, %1;" :: "n"(ID), "n"(N) : "memory"); }
DEVI void spin_guard(unsigned& n) { if (++n > SPIN_MAX) __trap(); }
DEVI uint4 ld_relaxed_v4(const void* p) {
    uint4 v;
    asm volatile("ld.relaxed.gpu.global.v4.u32 {%0,%1,%2,%3}, [%4];" : "=r"(v.x), "=r"(v.y), "=r"(v.z), "=r"(v.w) : "l"(p) : "memory");
    return v;
}
DEVI void st_relaxed_v4(void* p, const uint4& v) {
    asm volatile("st.relaxed.gpu.global.v4.u32 [%0], {%1,%2,%3,%4};" :: "l"(p), "r"(v.x), "r"(v.y), "r"(v.z), "r"(v.w) : "memory");
}
DEVI unsigned ld_relaxed_u32(const void* p) { unsigned v; asm volatile("ld.relaxed.gpu.global.u32 %0, [%1];" : "=r"(v) : "l"(p) : "memory"); return v; }
DEVI unsigned ld_acquire_u32(const void* p) { unsigned v; asm volatile("ld.acquire.gpu.global.u32 %0, [%1];" : "=r"(v) : "l"(p) : "memory"); return v; }
DEVI void st_relaxed_u32(void* p, unsigned v) { asm volatile("st.relaxed.gpu.global.u32 [%0], %1;" :: "l"(p), "r"(v) : "memory"); }
DEVI void st_relaxed_v2(void* p, unsigned a, unsigned b) { asm volatile("st.relaxed.gpu.global.v2.u32 [%0], {%1,%2};" :: "l"(p), "r"(a), "r"(b) : "memory"); }
DEVI uint4 ld_gen_v4(const void* p) {
    uint4 v;
    asm volatile("ld.relaxed.gpu.v4.u32 {%0,%1,%2,%3}, [%4];" : "=r"(v.x), "=r"(v.y), "=r"(v.z), "=r"(v.w) : "l"(p) : "memory");
    return v;
}
DEVI void st_gen_v4(void* p, const uint4& v) { asm volatile("st.relaxed.gpu.v4.u32 [%0], {%1,%2,%3,%4};" :: "l"(p), "r"(v.x), "r"(v.y), "r"(v.z), "r"(v.w) : "memory"); }
DEVI float sqrt_approx(float x) { float y; asm("sqrt.approx.ftz.f32 %0, %1;" : "=f"(y) : "f"(x)); return y; }
DEVI void red_add_u32(unsigned* p, unsigned v) { asm volatile("red.relaxed.gpu.global.add.u32 [%0], %1;" :: "l"(p), "r"(v) : "memory"); }
DEVI void red_add_v4(void* p, float a, float b, float c, float d) {
    asm volatile("red.relaxed.gpu.global.add.v4.f32 [%0], {%1,%2,%3,%4};" :: "l"(p), "f"(a), "f"(b), "f"(c), "f"(d) : "memory");
}
DEVI float4 ld_relaxed_f4(const void* p) {
    float4 v;
    asm volatile("ld.relaxed.gpu.global.v4.f32 {%0,%1,%2,%3}, [%4];" : "=f"(v.x), "=f"(v.y), "=f"(v.z), "=f"(v.w) : "l"(p) : "memory");
    return v;
}
DEVI void tma3d_store(const CUtensorMap* tm, uint32_t src, int c0, int c1, int c2) {
    asm volatile("cp.async.bulk.tensor.3d.global.shared::cta.bulk_group [%0, {%2, %3, %4}], [%1];\ncp.async.bulk.commit_group;\ncp.async.bulk.wait_group.read 0;"
                 :: "l"(tm), "r"(src), "r"(c0), "r"(c1), "r"(c2) : "memory");
}
DEVI uint32_t lds_u16(uint32_t a) { unsigned short v; asm volatile("ld.shared.u16 %0, [%1];" : "=h"(v) : "r"(a)); return v; }
DEVI void fence_gpu() { asm volatile("fence.acq_rel.gpu;" ::: "memory"); }
DEVI uint4 ldg_v4(const void* p) {
    uint4 v;
    asm volatile("ld.global.L1::no_allocate.v4.u32 {%0,%1,%2,%3}, [%4];" : "=r"(v.x), "=r"(v.y), "=r"(v.z), "=r"(v.w) : "l"(p) : "memory");
    return v;
}
DEVI uint4 lds_v4(uint32_t a) { uint4 v; asm volatile("ld.shared.v4.u32 {%0,%1,%2,%3}, [%4];" : "=r"(v.x), "=r"(v.y), "=r"(v.z), "=r"(v.w) : "r"(a)); return v; }
DEVI void sts_v4(uint32_t a, const uint4& v) { asm volatile("st.shared.v4.u32 [%0], {%1,%2,%3,%4};" :: "r"(a), "r"(v.x), "r"(v.y), "r"(v.z), "r"(v.w) : "memory"); }
DEVI void sts_f4(uint32_t a, float x, float y, float z, float w) { asm volatile("st.shared.v4.f32 [%0], {%1,%2,%3,%4};" :: "r"(a), "f"(x), "f"(y), "f"(z), "f"(w) : "memory"); }
DEVI float2 lds_f2(uint32_t a) { float2 v; asm volatile("ld.shared.v2.f32 {%0,%1}, [%2];" : "=f"(v.x), "=f"(v.y) : "r"(a)); return v; }
DEVI float4 lds_f4(uint32_t a) { float4 v; asm volatile("ld.shared.v4.f32 {%0,%1,%2,%3}, [%4];" : "=f"(v.x), "=f"(v.y), "=f"(v.z), "=f"(v.w) : "r"(a)); return v; }
DEVI void ldsm4(uint32_t addr, uint32_t& a, uint32_t& b, uint32_t& c, uint32_t& d) {
    asm volatile("ldmatrix.sync.aligned.m8n8.x4.shared.b16 {%0,%1,%2,%3}, [%4];" : "=r"(a), "=r"(b), "=r"(c), "=r"(d) : "r"(addr));
}
DEVI void ldsm4_if(bool on, uint32_t addr, uint32_t (&v)[4]) {
    asm volatile("{\n.reg .pred p;\nsetp.ne.b32 p, %5, 0;\n@p ldmatrix.sync.aligned.m8n8.x4.shared.b16 {%0,%1,%2,%3}, [%4];\n}"
                 : "+r"(v[0]), "+r"(v[1]), "+r"(v[2]), "+r"(v[3]) : "r"(addr), "r"((uint32_t)on));
}
DEVI void ldsm4t(uint32_t addr, uint32_t (&v)[4]) {
    asm volatile("ldmatrix.sync.aligned.m8n8.x4.trans.shared.b16 {%0,%1,%2,%3}, [%4];" : "=r"(v[0]), "=r"(v[1]), "=r"(v[2]), "=r"(v[3]) : "r"(addr));
}
DEVI void ldsm2(uint32_t addr, uint32_t& a, uint32_t& b) { asm volatile("ldmatrix.sync.aligned.m8n8.x2.shared.b16 {%0,%1}, [%2];" : "=r"(a), "=r"(b) : "r"(addr)); }
DEVI void cp_async16(uint32_t dst, const void* src) { asm volatile("cp.async.cg.shared.global [%0], [%1], 16;" :: "r"(dst), "l"(src) : "memory"); }
DEVI void prefetch_l2_bulk(const void* p, uint32_t bytes) { asm volatile("cp.async.bulk.prefetch.L2.global [%0], %1;" :: "l"(p), "r"(bytes) : "memory"); }
DEVI void sts_u16(uint32_t a, uint32_t v) { asm volatile("st.shared.u16 [%0], %1;" :: "r"(a), "h"((unsigned short)v) : "memory"); }
DEVI uint32_t hfma2(uint32_t a, uint32_t b, uint32_t c) { uint32_t d; asm("fma.rn.bf16x2 %0, %1, %2, %3;" : "=r"(d) : "r"(a), "r"(b), "r"(c)); return d; }
DEVI uint32_t imul(uint32_t a, uint32_t b) { uint32_t d; asm("mul.lo.u32 %0, %1, %2;" : "=r"(d) : "r"(a), "r"(b)); return d; }
DEVI float tanh_f(float x) { float t; asm("tanh.approx.f32 %0, %1;" : "=f"(t) : "f"(x)); return t; }
DEVI void stsm4(uint32_t addr, uint32_t a, uint32_t b, uint32_t c, uint32_t d) {
    asm volatile("stmatrix.sync.aligned.m8n8.x4.shared.b16 [%0], {%1,%2,%3,%4};" :: "r"(addr), "r"(a), "r"(b), "r"(c), "r"(d) : "memory");
}
DEVI uint32_t movm(uint32_t a) { uint32_t d; asm("movmatrix.sync.aligned.m8n8.trans.b16 %0, %1;" : "=r"(d) : "r"(a)); return d; }
DEVI void mma16(float (&c)[4], uint32_t a0, uint32_t a1, uint32_t a2, uint32_t a3, uint32_t b0, uint32_t b1) {
    asm("mma.sync.aligned.m16n8k16.row.col.f32.bf16.bf16.f32 {%0,%1,%2,%3}, {%4,%5,%6,%7}, {%8,%9}, {%0,%1,%2,%3};"
                 : "+f"(c[0]), "+f"(c[1]), "+f"(c[2]), "+f"(c[3]) : "r"(a0), "r"(a1), "r"(a2), "r"(a3), "r"(b0), "r"(b1));
}
DEVI void mma8(float (&c)[4], uint32_t a0, uint32_t a1, uint32_t b0) {
    asm("mma.sync.aligned.m16n8k8.row.col.f32.bf16.bf16.f32 {%0,%1,%2,%3}, {%4,%5}, {%6}, {%0,%1,%2,%3};"
                 : "+f"(c[0]), "+f"(c[1]), "+f"(c[2]), "+f"(c[3]) : "r"(a0), "r"(a1), "r"(b0));
}
DEVI uint32_t pack_bf16(float lo, float hi) { uint32_t d; asm("cvt.rn.bf16x2.f32 %0, %1, %2;" : "=r"(d) : "f"(hi), "f"(lo)); return d; }
DEVI float bf_lo(uint32_t v) { return __uint_as_float(v << 16); }
DEVI float bf_hi(uint32_t v) { return __uint_as_float(v & 0xffff0000u); }
DEVI float bfr(float x) { return __bfloat162float(__float2bfloat16_rn(x)); }
DEVI uint32_t tagf(float v, unsigned tag) { return (__float_as_uint(v) & ~15u) | (tag & 15); }
DEVI float ex2(float x) { float y; asm("ex2.approx.ftz.f32 %0, %1;" : "=f"(y) : "f"(x)); return y; }
DEVI float rcp(float x) { float y; asm("rcp.approx.ftz.f32 %0, %1;" : "=f"(y) : "f"(x)); return y; }
DEVI float sigmoid_f(float x) { return rcp(1.0f + ex2(x * -1.4426950408889634f)); }
DEVI float silu_f(float x) { const float h = 0.5f * x; float t; asm("tanh.approx.f32 %0, %1;" : "=f"(t) : "f"(h)); return fmaf(h, t, h); }
DEVI uint32_t hsub2(uint32_t a, uint32_t b) { uint32_t d; asm("sub.rn.bf16x2 %0, %1, %2;" : "=r"(d) : "r"(a), "r"(b)); return d; }
DEVI uint32_t hadd2(uint32_t a, uint32_t b) { uint32_t d; asm("add.rn.bf16x2 %0, %1, %2;" : "=r"(d) : "r"(a), "r"(b)); return d; }
DEVI uint32_t hmul2(uint32_t a, uint32_t b) { uint32_t d; asm("mul.rn.bf16x2 %0, %1, %2;" : "=r"(d) : "r"(a), "r"(b)); return d; }
DEVI uint32_t dup_hi(float x) { return __byte_perm(__float_as_uint(x), 0, 0x3232); }
DEVI void sts_u32(uint32_t a, uint32_t v) { asm volatile("st.shared.u32 [%0], %1;" :: "r"(a), "r"(v) : "memory"); }
DEVI void sts_f2(uint32_t a, float x, float y) { asm volatile("st.shared.v2.f32 [%0], {%1,%2};" :: "r"(a), "f"(x), "f"(y) : "memory"); }
DEVI uint2 lds_v2(uint32_t a) { uint2 v; asm volatile("ld.shared.v2.u32 {%0,%1}, [%2];" : "=r"(v.x), "=r"(v.y) : "r"(a)); return v; }
DEVI uint32_t lds_u32(uint32_t a) { uint32_t v; asm volatile("ld.shared.u32 %0, [%1];" : "=r"(v) : "r"(a)); return v; }
DEVI float lds_f32(uint32_t a) { float v; asm volatile("ld.shared.f32 %0, [%1];" : "=f"(v) : "r"(a)); return v; }
DEVI float shfl_x(float v, int o) { return __shfl_xor_sync(0xffffffffu, v, o); }

DEVI void wgmma_rs_n192(float (&d)[120], uint32_t a0, uint32_t a1, uint32_t a2, uint32_t a3, uint32_t blo, uint32_t scale_d) {
    asm volatile("{\n.reg .b64 db;\n.reg .pred p;\n"
        "setp.ne.b32 p, %101, 0;\n"
        "mov.b64 db, {%100, 0x40000040};\n"
        "wgmma.mma_async.sync.aligned.m64n192k16.f32.bf16.bf16 "
        "{%0, %1, %2, %3, %4, %5, %6, %7, %8, %9, %10, %11, %12, %13, %14, %15, %16, %17, %18, %19, %20, %21, %22, %23, %24, %25, %26, %27, %28, %29, %30, %31, %32, %33, %34, %35, %36, %37, %38, %39, %40, %41, %42, %43, %44, %45, %46, %47, %48, %49, %50, %51, %52, %53, %54, %55, %56, %57, %58, %59, %60, %61, %62, %63, %64, %65, %66, %67, %68, %69, %70, %71, %72, %73, %74, %75, %76, %77, %78, %79, %80, %81, %82, %83, %84, %85, %86, %87, %88, %89, %90, %91, %92, %93, %94, %95}, "
        "{%96, %97, %98, %99}, db, p, 1, 1, 1;\n}\n"
        : "+f"(d[0]), "+f"(d[1]), "+f"(d[2]), "+f"(d[3]), "+f"(d[4]), "+f"(d[5]), "+f"(d[6]), "+f"(d[7]), "+f"(d[8]), "+f"(d[9]), "+f"(d[10]), "+f"(d[11]), "+f"(d[12]), "+f"(d[13]), "+f"(d[14]), "+f"(d[15]), "+f"(d[16]), "+f"(d[17]), "+f"(d[18]), "+f"(d[19]), "+f"(d[20]), "+f"(d[21]), "+f"(d[22]), "+f"(d[23]), "+f"(d[24]), "+f"(d[25]), "+f"(d[26]), "+f"(d[27]), "+f"(d[28]), "+f"(d[29]), "+f"(d[30]), "+f"(d[31]), "+f"(d[32]), "+f"(d[33]), "+f"(d[34]), "+f"(d[35]), "+f"(d[36]), "+f"(d[37]), "+f"(d[38]), "+f"(d[39]), "+f"(d[40]), "+f"(d[41]), "+f"(d[42]), "+f"(d[43]), "+f"(d[44]), "+f"(d[45]), "+f"(d[46]), "+f"(d[47]), "+f"(d[48]), "+f"(d[49]), "+f"(d[50]), "+f"(d[51]), "+f"(d[52]), "+f"(d[53]), "+f"(d[54]), "+f"(d[55]), "+f"(d[56]), "+f"(d[57]), "+f"(d[58]), "+f"(d[59]), "+f"(d[60]), "+f"(d[61]), "+f"(d[62]), "+f"(d[63]), "+f"(d[64]), "+f"(d[65]), "+f"(d[66]), "+f"(d[67]), "+f"(d[68]), "+f"(d[69]), "+f"(d[70]), "+f"(d[71]), "+f"(d[72]), "+f"(d[73]), "+f"(d[74]), "+f"(d[75]), "+f"(d[76]), "+f"(d[77]), "+f"(d[78]), "+f"(d[79]), "+f"(d[80]), "+f"(d[81]), "+f"(d[82]), "+f"(d[83]), "+f"(d[84]), "+f"(d[85]), "+f"(d[86]), "+f"(d[87]), "+f"(d[88]), "+f"(d[89]), "+f"(d[90]), "+f"(d[91]), "+f"(d[92]), "+f"(d[93]), "+f"(d[94]), "+f"(d[95])
        : "r"(a0), "r"(a1), "r"(a2), "r"(a3), "r"(blo), "r"(scale_d));
}
DEVI void wgmma_rs_n48(float (&d)[120], uint32_t a0, uint32_t a1, uint32_t a2, uint32_t a3, uint32_t blo, uint32_t scale_d) {
    asm volatile("{\n.reg .b64 db;\n.reg .pred p;\n"
        "setp.ne.b32 p, %29, 0;\n"
        "mov.b64 db, {%28, 0xc0000010};\n"
        "wgmma.mma_async.sync.aligned.m64n48k16.f32.bf16.bf16 "
        "{%0, %1, %2, %3, %4, %5, %6, %7, %8, %9, %10, %11, %12, %13, %14, %15, %16, %17, %18, %19, %20, %21, %22, %23}, "
        "{%24, %25, %26, %27}, db, p, 1, 1, 1;\n}\n"
        : "+f"(d[96]), "+f"(d[97]), "+f"(d[98]), "+f"(d[99]), "+f"(d[100]), "+f"(d[101]), "+f"(d[102]), "+f"(d[103]), "+f"(d[104]), "+f"(d[105]), "+f"(d[106]), "+f"(d[107]), "+f"(d[108]), "+f"(d[109]), "+f"(d[110]), "+f"(d[111]), "+f"(d[112]), "+f"(d[113]), "+f"(d[114]), "+f"(d[115]), "+f"(d[116]), "+f"(d[117]), "+f"(d[118]), "+f"(d[119])
        : "r"(a0), "r"(a1), "r"(a2), "r"(a3), "r"(blo), "r"(scale_d));
}
DEVI void wgmma_rs_n192x(float (&d)[120], uint32_t a0, uint32_t a1, uint32_t a2, uint32_t a3, uint32_t blo) {
    asm volatile("{\n.reg .b64 db;\n.reg .pred p;\n"
        "mov.b64 db, {%100, 0x40000000};\n"
        "wgmma.mma_async.sync.aligned.m64n192k16.f32.bf16.bf16 "
        "{%0, %1, %2, %3, %4, %5, %6, %7, %8, %9, %10, %11, %12, %13, %14, %15, %16, %17, %18, %19, %20, %21, %22, %23, %24, %25, %26, %27, %28, %29, %30, %31, %32, %33, %34, %35, %36, %37, %38, %39, %40, %41, %42, %43, %44, %45, %46, %47, %48, %49, %50, %51, %52, %53, %54, %55, %56, %57, %58, %59, %60, %61, %62, %63, %64, %65, %66, %67, %68, %69, %70, %71, %72, %73, %74, %75, %76, %77, %78, %79, %80, %81, %82, %83, %84, %85, %86, %87, %88, %89, %90, %91, %92, %93, %94, %95}, "
        "{%96, %97, %98, %99}, db, 1, 1, 1, 1;\n}\n"
        : "+f"(d[0]), "+f"(d[1]), "+f"(d[2]), "+f"(d[3]), "+f"(d[4]), "+f"(d[5]), "+f"(d[6]), "+f"(d[7]), "+f"(d[8]), "+f"(d[9]), "+f"(d[10]), "+f"(d[11]), "+f"(d[12]), "+f"(d[13]), "+f"(d[14]), "+f"(d[15]), "+f"(d[16]), "+f"(d[17]), "+f"(d[18]), "+f"(d[19]), "+f"(d[20]), "+f"(d[21]), "+f"(d[22]), "+f"(d[23]), "+f"(d[24]), "+f"(d[25]), "+f"(d[26]), "+f"(d[27]), "+f"(d[28]), "+f"(d[29]), "+f"(d[30]), "+f"(d[31]), "+f"(d[32]), "+f"(d[33]), "+f"(d[34]), "+f"(d[35]), "+f"(d[36]), "+f"(d[37]), "+f"(d[38]), "+f"(d[39]), "+f"(d[40]), "+f"(d[41]), "+f"(d[42]), "+f"(d[43]), "+f"(d[44]), "+f"(d[45]), "+f"(d[46]), "+f"(d[47]), "+f"(d[48]), "+f"(d[49]), "+f"(d[50]), "+f"(d[51]), "+f"(d[52]), "+f"(d[53]), "+f"(d[54]), "+f"(d[55]), "+f"(d[56]), "+f"(d[57]), "+f"(d[58]), "+f"(d[59]), "+f"(d[60]), "+f"(d[61]), "+f"(d[62]), "+f"(d[63]), "+f"(d[64]), "+f"(d[65]), "+f"(d[66]), "+f"(d[67]), "+f"(d[68]), "+f"(d[69]), "+f"(d[70]), "+f"(d[71]), "+f"(d[72]), "+f"(d[73]), "+f"(d[74]), "+f"(d[75]), "+f"(d[76]), "+f"(d[77]), "+f"(d[78]), "+f"(d[79]), "+f"(d[80]), "+f"(d[81]), "+f"(d[82]), "+f"(d[83]), "+f"(d[84]), "+f"(d[85]), "+f"(d[86]), "+f"(d[87]), "+f"(d[88]), "+f"(d[89]), "+f"(d[90]), "+f"(d[91]), "+f"(d[92]), "+f"(d[93]), "+f"(d[94]), "+f"(d[95])
        : "r"(a0), "r"(a1), "r"(a2), "r"(a3), "r"(blo));
}
DEVI void wgmma_rs_n48x(float (&d)[120], uint32_t a0, uint32_t a1, uint32_t a2, uint32_t a3, uint32_t blo) {
    asm volatile("{\n.reg .b64 db;\n.reg .pred p;\n"
        "mov.b64 db, {%28, 0xc0000000};\n"
        "wgmma.mma_async.sync.aligned.m64n48k16.f32.bf16.bf16 "
        "{%0, %1, %2, %3, %4, %5, %6, %7, %8, %9, %10, %11, %12, %13, %14, %15, %16, %17, %18, %19, %20, %21, %22, %23}, "
        "{%24, %25, %26, %27}, db, 1, 1, 1, 1;\n}\n"
        : "+f"(d[96]), "+f"(d[97]), "+f"(d[98]), "+f"(d[99]), "+f"(d[100]), "+f"(d[101]), "+f"(d[102]), "+f"(d[103]), "+f"(d[104]), "+f"(d[105]), "+f"(d[106]), "+f"(d[107]), "+f"(d[108]), "+f"(d[109]), "+f"(d[110]), "+f"(d[111]), "+f"(d[112]), "+f"(d[113]), "+f"(d[114]), "+f"(d[115]), "+f"(d[116]), "+f"(d[117]), "+f"(d[118]), "+f"(d[119])
        : "r"(a0), "r"(a1), "r"(a2), "r"(a3), "r"(blo));
}
DEVI void wgmma_rs_n80(float (&d)[40], uint32_t a0, uint32_t a1, uint32_t a2, uint32_t a3, uint32_t blo, uint32_t scale_d) {
    asm volatile("{\n.reg .b64 db;\n.reg .pred p;\n"
        "setp.ne.b32 p, %45, 0;\n"
        "mov.b64 db, {%44, 0x40000040};\n"
        "wgmma.mma_async.sync.aligned.m64n80k16.f32.bf16.bf16 "
        "{%0, %1, %2, %3, %4, %5, %6, %7, %8, %9, %10, %11, %12, %13, %14, %15, %16, %17, %18, %19, %20, %21, %22, %23, %24, %25, %26, %27, %28, %29, %30, %31, %32, %33, %34, %35, %36, %37, %38, %39}, "
        "{%40, %41, %42, %43}, db, p, 1, 1, 1;\n}\n"
        : "+f"(d[0]), "+f"(d[1]), "+f"(d[2]), "+f"(d[3]), "+f"(d[4]), "+f"(d[5]), "+f"(d[6]), "+f"(d[7]), "+f"(d[8]), "+f"(d[9]), "+f"(d[10]), "+f"(d[11]), "+f"(d[12]), "+f"(d[13]), "+f"(d[14]), "+f"(d[15]), "+f"(d[16]), "+f"(d[17]), "+f"(d[18]), "+f"(d[19]), "+f"(d[20]), "+f"(d[21]), "+f"(d[22]), "+f"(d[23]), "+f"(d[24]), "+f"(d[25]), "+f"(d[26]), "+f"(d[27]), "+f"(d[28]), "+f"(d[29]), "+f"(d[30]), "+f"(d[31]), "+f"(d[32]), "+f"(d[33]), "+f"(d[34]), "+f"(d[35]), "+f"(d[36]), "+f"(d[37]), "+f"(d[38]), "+f"(d[39])
        : "r"(a0), "r"(a1), "r"(a2), "r"(a3), "r"(blo), "r"(scale_d));
}
DEVI void wgmma_ss_n80(float (&d)[40], uint32_t alo, uint32_t blo) {
    asm volatile("{\n.reg .b64 da, db;\n"
        "mov.b64 da, {%40, 0x10};\n"
        "mov.b64 db, {%41, 0x40000040};\n"
        "wgmma.mma_async.sync.aligned.m64n80k16.f32.bf16.bf16 "
        "{%0, %1, %2, %3, %4, %5, %6, %7, %8, %9, %10, %11, %12, %13, %14, %15, %16, %17, %18, %19, %20, %21, %22, %23, %24, %25, %26, %27, %28, %29, %30, %31, %32, %33, %34, %35, %36, %37, %38, %39}, "
        "da, db, 1, 1, 1, 0, 1;\n}\n"
        : "+f"(d[0]), "+f"(d[1]), "+f"(d[2]), "+f"(d[3]), "+f"(d[4]), "+f"(d[5]), "+f"(d[6]), "+f"(d[7]), "+f"(d[8]), "+f"(d[9]), "+f"(d[10]), "+f"(d[11]), "+f"(d[12]), "+f"(d[13]), "+f"(d[14]), "+f"(d[15]), "+f"(d[16]), "+f"(d[17]), "+f"(d[18]), "+f"(d[19]), "+f"(d[20]), "+f"(d[21]), "+f"(d[22]), "+f"(d[23]), "+f"(d[24]), "+f"(d[25]), "+f"(d[26]), "+f"(d[27]), "+f"(d[28]), "+f"(d[29]), "+f"(d[30]), "+f"(d[31]), "+f"(d[32]), "+f"(d[33]), "+f"(d[34]), "+f"(d[35]), "+f"(d[36]), "+f"(d[37]), "+f"(d[38]), "+f"(d[39])
        : "r"(alo), "r"(blo));
}

DEVI unsigned redux_max(unsigned v) { return __reduce_max_sync(0xffffffffu, v); }

DEVI void service_cta(Scratch* __restrict__ sc, const __nv_bfloat16* __restrict__ x, const __nv_bfloat16* __restrict__ wr, uint32_t sb, int h, int tid) {
    const int warp = tid >> 5, lane = tid & 31;
    Outbox* const box = &sc->box[h];
    const unsigned tag = ld_relaxed_u32(&sc->epoch[(NCTA + h) * 32]) + 1;
    if (tid < 256) st_relaxed_v4(&box->msg[0] + tid, make_uint4(EMPTY_WORD, EMPTY_WORD, EMPTY_WORD, EMPTY_WORD));
    __syncthreads();
    unsigned spins = 0;
    if (warp == 0) {
        fence_gpu();
        if (lane < 2) st_relaxed_v4(&sc->open[h][lane * 4], make_uint4(tag, tag, tag, tag));
    }
    if (warp >= 8) {
        const int t = tid - 256;
        float wsum = 0.f;
        __nanosleep(1000);
#pragma unroll
        for (int j = 0; j < 10; j++) { const uint32_t v = reinterpret_cast<const uint32_t*>(wr)[lane + 32 * j]; wsum += bf_lo(v) + bf_hi(v); }
#pragma unroll
        for (int o = 1; o < 32; o <<= 1) wsum += shfl_x(wsum, o);
        uint4 q[4];
        const uint4* src = reinterpret_cast<const uint4*>(&sc->rowinfo[0][0][0]) + t;
#pragma unroll
        for (int j = 0; j < 4; j++) q[j].y = q[j].w = tag - 1;
        while (true) {
            unsigned bad = 0;
#pragma unroll
            for (int j = 0; j < 4; j++) if (((q[j].y ^ tag) | (q[j].w ^ tag)) & 15) q[j] = ld_relaxed_v4(src + 256 * j);
            __syncwarp();
#pragma unroll
            for (int j = 0; j < 4; j++) bad |= (q[j].y ^ tag) | (q[j].w ^ tag);
            if (__all_sync(0xffffffffu, (bad & 15) == 0)) break;
            if (spins == 0) while (!__any_sync(0xffffffffu, ((ld_relaxed_v4(src).y ^ tag) & 15) == 0)) { __nanosleep(100); spin_guard(spins); }
            spin_guard(spins);
        }
        if (t == 0) TL(2);
        unsigned a = 0, b = 0;
#pragma unroll
        for (int j = 0; j < 8; j++) {
            const uint32_t info = (j & 1) ? q[j >> 1].z : q[j >> 1].x;
            const uint32_t u = pack_bf16(fmaf(-bf_lo(info), wsum, __uint_as_float((j & 1) ? q[j >> 1].w : q[j >> 1].y)) * rcp(bf_hi(info)), 0.f);
            const int row = ((j >> 1) * 4 + (t >> 6)) * 128 + 4 * (t & 31) + 2 * (j & 1) + ((t >> 5) & 1);
            const unsigned key = (((u & 0x8000u) ? (u ^ 0xffffu) : (u | 0x8000u)) << 16) | ((2047 - row) << 5);
            b = max(b, min(a, key)); a = max(a, key);
        }
        unsigned k1 = redux_max(a), k2 = redux_max(a == k1 ? b : a);
        if (lane == 0) sts_f2(sb + 8192 + (warp - 8) * 8, __uint_as_float(k1), __uint_as_float(k2));
        bar_sync<2, 256>();
        a = lds_u32(sb + 8192 + (lane & 15) * 4);
        k1 = redux_max(a); k2 = redux_max(a == k1 ? 0u : a);
        if (t < 160) {
            const int tk = t >= 80, sel = 2047 - (((tk ? k2 : k1) >> 5) & 2047);
            const uint4 xq = ldg_v4(reinterpret_cast<const uint4*>(x + sel * DM) + t - tk * 80);
            const unsigned info = ld_relaxed_u32(&sc->rowinfo[sel >> 7][sel & 1][(sel & 127) >> 1]);
            const uint32_t mm = __byte_perm(info, 0, 0x1010);
            const float rs = rcp(bf_hi(info));
            uint32_t o[4];
#pragma unroll
            for (int e = 0; e < 4; e++) { const uint32_t d = hsub2((&xq.x)[e], mm); o[e] = pack_bf16(bf_lo(d) * rs, bf_hi(d) * rs); }
            st_relaxed_v4(&box->msg[t + tk], make_uint4(o[0], o[1], o[2], o[3]));
            sts_v4(sb + SM_XSEL + (t + tk) * 16, make_uint4(o[0], o[1], o[2], o[3]));
        } else if (t == 160) {
            const uint4 top = make_uint4(2047 - ((k1 >> 5) & 2047), 2047 - ((k2 >> 5) & 2047), k1, k2);
            st_relaxed_v4(&box->msg[80], top); sts_v4(sb + SM_TOP, top);
        }
        if (t == 0) TL(3);
    }
    __syncthreads();
    const uint4* src = &sc->yp[2 * h + (warp >> 3)][warp & 7][0];
    uint4 v[7]; unsigned u[7];
#pragma unroll
    for (int j = 0; j < 7; j++) v[j].x = u[j] = (j == 6 && (warp & 7) >= 6) ? tag : tag - 1;
    spins = 0;
    while (NMOE) {
        unsigned bad = 0;
#pragma unroll
        for (int j = 0; j < 7; j++)
            if (((v[j].x ^ tag) | (u[j] ^ tag)) & 15) { v[j] = ld_relaxed_v4(src + j * 320 + lane); u[j] = ld_relaxed_u32(reinterpret_cast<const unsigned*>(src + j * 320 + 32) + lane); }
        __syncwarp();
#pragma unroll
        for (int j = 0; j < 7; j++) bad |= (v[j].x ^ tag) | (u[j] ^ tag);
        if (__all_sync(0xffffffffu, (bad & 15) == 0)) break;
        if (spins == 0) while (!__any_sync(0xffffffffu, ((ld_relaxed_u32(src + min(lane & 7, 5) * 320 + 32) ^ tag) & 15) == 0)) { __nanosleep(100); spin_guard(spins); }
        spin_guard(spins);
    }
    if (tid == 0) TL(4);
    float y[5] = {0.f, 0.f, 0.f, 0.f, 0.f};
#pragma unroll
    for (int j = 0; j < 7; j++) {
        if (NMOE && (j < 6 || (warp & 7) < 6)) {
            y[0] += __uint_as_float(v[j].x); y[1] += __uint_as_float(v[j].y); y[2] += __uint_as_float(v[j].z); y[3] += __uint_as_float(v[j].w); y[4] += __uint_as_float(u[j]);
        }
    }
#pragma unroll
    for (int e = 0; e < 5; e++) sts_u32(sb + (warp * 160 + e * 32 + lane) * 4, __float_as_uint(y[e]));
    __syncthreads();
    if (warp < 10) {
        const int gi = warp >= 5, e = warp - 5 * gi, tk = lane & 1, col = e * 16 + (lane >> 2) + 4 * (lane & 2);
        float sum = 0.f;
#pragma unroll
        for (int j = 0; j < 8; j++) sum += lds_f32(sb + ((gi * 8 + j) * 160 + e * 32 + lane) * 4);
        const uint32_t ks = lds_u32(sb + SM_TOP + 8 + tk * 4) >> 16;
        const float sg = bfr(sigmoid_f(__uint_as_float(((ks & 0x8000u) ? (ks & 0x7fffu) : (ks ^ 0xffffu)) << 16)));
        sts_u16(sb + 16384 + gi * 512 + tk * 160 + col * 2,
                pack_bf16(silu_f(bfr(bf_lo(lds_u16(sb + SM_XSEL + tk * 1296 + ((2 * h + gi) * 80 + col) * 2)) + bfr(bfr(sum) * sg))), 0.f));
        bar_sync<1, 320>();
        if (warp < 2 && lane < 20) st_relaxed_v4(&box->gt[warp][lane], lds_v4(sb + 16384 + tid * 16));
    }
    if (tid == 0) { st_relaxed_u32(&sc->epoch[(NCTA + h) * 32], tag); TL(5); }
}

template <int ODD, int HALF> DEVI void pack_kv(const float (&acc)[120], uint32_t (&K)[10][2], uint32_t (&V)[10][2]) {
#pragma unroll
    for (int b = 0; b < 10; b++) {
        const int pb = ODD ? (b + 8) % 10 : b, jk = pb < 8 ? 8 + pb : 18 + pb, jv = pb < 8 ? 16 + pb : 20 + pb;
        V[b][HALF] = movm(pack_bf16(acc[4 * jv + 2 * HALF], acc[4 * jv + 2 * HALF + 1]));
        K[b][HALF] = pack_bf16(acc[4 * jk + 2 * HALF], acc[4 * jk + 2 * HALF + 1]);
    }
}
template <int ODD> DEVI void pack_q(const float (&acc)[120], uint32_t (&Q)[10][2]) {
#pragma unroll
    for (int b = 0; b < 10; b++) {
        const int pb = ODD ? (b + 8) % 10 : b, jq = pb < 8 ? pb : 16 + pb;
        Q[b][0] = pack_bf16(acc[4 * jq], acc[4 * jq + 1]); Q[b][1] = pack_bf16(acc[4 * jq + 2], acc[4 * jq + 3]);
    }
}

#define KROT 5
#define WOP 8
#define SIDE_N -1
#define PIPE_POLL 0
#define NSIDE 4
#define WO_S 6
#define TAIL_NS 50
#define WO_GATE 0
#define MSG_NS 1500
#define GI_T 0
#define SPLIT 3
#define RS_PACE(t) (t)
#define ATS(i)
#define SRC(i) ((i) == 0 ? g : ((i) - 1 < g ? (i) - 1 : (i)))

__global__ void __cluster_dims__(2, 1, 1) __launch_bounds__(NTHREADS, 1) fused_kernel(
    Scratch* __restrict__ sc,
    const __nv_bfloat16* __restrict__ x, const __nv_bfloat16* __restrict__ wqkv, const __nv_bfloat16* __restrict__ wo, const __nv_bfloat16* __restrict__ wr,
    const __nv_bfloat16* __restrict__ wd, __nv_bfloat16* __restrict__ out, const int by_sm, const __grid_constant__ Roles roles,
    const __grid_constant__ CUtensorMap tm_x, const __grid_constant__ CUtensorMap tm_w, const __grid_constant__ CUtensorMap tm_wt,
    const __grid_constant__ CUtensorMap tm_wo, const __grid_constant__ CUtensorMap tm_d,
    const __grid_constant__ CUtensorMap tm_g, const __grid_constant__ CUtensorMap tm_u, const __grid_constant__ CUtensorMap tm_o)
{
    extern __shared__ __align__(1024) unsigned char smem[];
    uint32_t sb, smid;
    asm volatile("mov.u32 %0, %1;" : "=r"(sb) : "r"(smem_u32(smem)));
    asm volatile("mov.u32 %0, %%smid;" : "=r"(smid));
    const uint32_t bid = blockIdx.x, tid = threadIdx.x;
    const unsigned cta = roles.pair[(by_sm ? smid : bid) >> 1] * 2 + (bid & 1);
    const int warp = __shfl_sync(0xffffffffu, tid >> 5, 0), lane = tid & 31;
    const uint32_t bars = sb + SM_BAR;
    if (warp == 8) {
        if (elect_one()) {
            mbar_init(bars + BAR_FA * 8, 1);
            asm volatile("fence.mbarrier_init.release.cluster;" ::: "memory");
        }
        __syncwarp();
    }
    if (warp == 9) {
        if (elect_one()) {
#pragma unroll
            for (int s = 0; s < NBAR; s++) if (s != BAR_FA) mbar_init(bars + s * 8, (s >> 2) == 1 ? 4 : (s >= BAR_AE ? (s >= BAR_FA ? 1 : (s == BAR_AE + 5 ? 2 : 4)) : (s >= BAR_PA ? 8 : (s == BAR_CS ? 4 : (s >= BAR_OE + 2 ? 2 : 1)))));
            asm volatile("fence.mbarrier_init.release.cluster;" ::: "memory");
        }
        __syncwarp();
    }
    cluster_arrive();
#define NPF 1
#define NPFX 1
    if (warp < NPF && bid < NCTA) {
        if (warp) __nanosleep(PF1_NS * warp);
        const char* qw = reinterpret_cast<const char*>(wqkv) + ((warp + (lane >= 15 ? KROT : 0)) * 1920 + bid * 15 + (lane >= 15 ? lane - 15 : lane)) * 128;
        const char* qx = lane < 16 ? reinterpret_cast<const char*>(x) + (bid * 16 + lane) * 1280 + (warp + ((bid >> 4) & 1) * KROT) * 128 : reinterpret_cast<const char*>(wr) + (lane - 16) * 128;
        if (lane < 30) asm volatile("prefetch.global.L2 [%0];" :: "l"(qw) : "memory");
        if (warp < NPFX && (lane < 16 || (bid == 0 && lane < 26))) asm volatile("prefetch.global.L2 [%0];" :: "l"(qx) : "memory");
    }
    if (cta >= NCTA) { cluster_wait(); service_cta(sc, x, wr, sb, cta - NCTA, tid); return; }
    const int rank = cta & 1, g = (cta >> 1) & 7, G = cta >> 4, m = 2 * G + rank, odd = g & 1;
    const int k0 = (G & 1) * KROT * 64;
    const int cm = g * 80 + odd * 16, ct = g * 80 + 64 - odd * 64;

#define NP0 2
#define TILE_X(kt, kk) tma3d(sb + (-(kt) & 3) * STAGE, &tm_x, bars + (BAR_FA + ((kt) & 3)) * 8, kk, m * 64, 0)
#define TILE_W(kt, kk) do { const uint32_t fb_ = bars + (BAR_FULL + ((kt) & 3)) * 8, st_ = sb + (-(kt) & 3) * STAGE + OFF_B; \
        tma3d_mc(st_ + rank * B_HALF, &tm_w, fb_, cm, (kk) + rank * 32, 0); \
        tma3d(st_ + 12288, &tm_wt, fb_, ct, kk, 0); tma3d(st_ + B_HALF + 12288, &tm_wt, fb_, ct, (kk) + 32, 0); } while (0)
    if (warp == 8) {
        if (elect_one()) { mbar_expect_tx(bars + BAR_FA * 8, OFF_B); TILE_X(0, k0); }
        cluster_wait();
        if (elect_one()) {
            mbar_expect_tx(bars + BAR_FULL * 8, 2 * B_HALF);
            TILE_W(0, k0);
            mbar_expect_tx(bars + BAR_WR * 8, 1280); bulk_load(sb + SM_XSEL, wr, 1280, bars + BAR_WR * 8);
            TL(16);
#pragma unroll
            for (int kt = 1; kt < NP0; kt++) {
                mbar_expect_tx(bars + (BAR_FA + kt) * 8, OFF_B); mbar_expect_tx(bars + (BAR_FULL + kt) * 8, 2 * B_HALF);
                TILE_X(kt, k0 + kt * 64); TILE_W(kt, k0 + kt * 64);
                if (kt == 1) TL(29);
            }
        }
        __syncwarp();
    }
    if (warp >= 8) {
        asm volatile("setmaxnreg.dec.sync.aligned.u32 64;");
        const int mi = g < 6 ? G * 6 + g : 46 + G;
        const bool moe = g < 6 || (g == 6 && G >= 2);
        if (warp == 8) {
            const CUtensorMap* tm_gu = rank ? &tm_u : &tm_g;
            if (elect_one()) { mbar_expect_tx(bars + BAR_WO * 8, 81920); mbar_expect_tx(bars + BAR_GW * 8, 40960); mbar_expect_tx(bars + BAR_DW * 8, 20480); }
#pragma unroll 1
            for (int kt = NP0; kt < 13; kt++) {
                if (kt >= 4) { mbar_wait(bars + (BAR_AE + min(kt, 9) - 4) * 8, 0); mbar_wait(bars + (BAR_EMPTY + (kt & 3)) * 8, ((kt >> 2) - 1) & 1); }
                if (elect_one()) {
                    if (kt < 10) {
                        const int kk = kt * 64 + (kt < 5 ? k0 : -k0);
                        mbar_expect_tx(bars + (BAR_FA + (kt & 3)) * 8, OFF_B); mbar_expect_tx(bars + (BAR_FULL + (kt & 3)) * 8, 2 * B_HALF);
                        TILE_X(kt, kk); TILE_W(kt, kk);
                        if (kt == WOP) prefetch_l2_bulk(reinterpret_cast<const char*>(wo) + cta * 6400, 6400);
                    }
                    if (moe) {
                        if (kt >= 4 && kt < 12) tma2d(sb + (kt == 11 ? SM_G7 : SM_MW + (kt - 4) * 5120), tm_gu, bars + BAR_GW * 8, mi * 32, (kt - 4) * 80);
                        if ((unsigned)(kt - DP0) < 2u) prefetch_l2_bulk(wd + (mi * 32 + rank * 16 + (kt - DP0) * 8) * DM, 10240);
                        if (kt == 12) {
#pragma unroll 1
                            for (int i = 0; i < 5; i++) tma2d(sb + SM_DW + i * 4096, &tm_d, bars + BAR_DW * 8, (rank * 5 + i) * 64, mi * 32);
                        }
                    }
                    if (kt == 3) TL(17);
                }
                __syncwarp();
                if (kt >= 10) {
                    if (kt == 11 && (WO_GATE & 2)) mbar_wait(bars + BAR_RS * 8, 0);
                    if (kt == 12 && (WO_GATE & 4)) mbar_wait(bars + BAR_SEL * 8, 0);
                    if (elect_one()) {
#pragma unroll 1
                        for (int i = (kt == 10 ? 0 : (kt == 11 ? 2 : WO_S)) + rank; i < (kt == 10 ? 2 : (kt == 11 ? WO_S : 8)); i += 2)
                            tma2d_mc(sb + SM_WO + (7 - i) * 10240, &tm_wo, bars + BAR_WO * 8, cm, SRC(i) * 80);
                    }
                    __syncwarp();
                }
            }
            const uint4* os = &sc->o[m][0][0][0];
            const unsigned* fl = &sc->flag[m][(lane & 7) == g ? g ^ 1 : lane & 7][0];
            const uint4* os2 = os + (g + 1) * 256;
            const uint32_t n1 = g * 4096, n2 = 28672 - n1;
            asm volatile("" : "+l"(fl));
            if (elect_one()) {
#pragma unroll
                for (int t = 0; t < 5; t++) mbar_expect_tx(bars + (BAR_OF + t) * 8, 28672);
            }
            mbar_wait(bars + (BAR_EMPTY + 1) * 8, 0);
            mbar_wait(bars + BAR_PA * 8, 0);
            unsigned lvl = 0, spins = 0;
#pragma unroll
            for (int t = 0; t < 5; t++) {
                while (__any_sync(0xffffffffu, lvl <= t)) {
                    lvl = ld_relaxed_u32(fl);
                    spin_guard(spins);
                }
                if (t) mbar_wait(bars + (BAR_OE + t - 1) * 8, 0);
                if (elect_one()) {
                    const uint32_t dst = sb + (t == 2 ? SM_O2 : ((t == 0 || t == 3) ? SM_O0 : SM_O1)), fb = bars + (BAR_OF + t) * 8;
                    if (g > 0) bulk_load(dst, os + t * 2048, n1, fb);
                    if (g < 7) bulk_load(dst + n1, os2 + t * 2048, n2, fb);
                    if (t == GI_T) mbar_arrive(bars + BAR_GI * 8);
                    TL(48 + t);
                }
                __syncwarp();
            }
        } else {
            const int ta = tid - 288, wa = warp - 9, c = lane & 3, r = lane >> 2;
            const unsigned tag = ld_relaxed_u32(&sc->epoch[cta * 32]) + 1;
            const Outbox* const box = &sc->box[g >> 1];
            unsigned spins = 0;
            if (wa == 0) {
                uint4 *ro = &sc->o[m][0][g][lane], *rh = &sc->halo[m * 8 + g][lane];
                if (lane < 2) st_relaxed_v4(&sc->rdone[m * 8 + g][lane * 4], make_uint4(0, 0, 0, 0));
                cluster_wait();
                if (lane == 0) mbar_expect_tx(bars + BAR_PX * 8, 256);
#pragma unroll 1
                for (int t = 0; t < 5; t++, ro += 2048, rh += 64) {
                    mbar_wait(bars + (BAR_AE + RS_PACE(t)) * 8, 0);
                    const uint4 e = make_uint4(EMPTY_WORD, EMPTY_WORD, EMPTY_WORD, EMPTY_WORD);
#pragma unroll
                    for (int i = 0; i < 8; i++) st_relaxed_v4(ro + 32 * i, e);
                    st_relaxed_v4(rh, e); st_relaxed_v4(rh + 32, e);
                }
                if (lane < 2) st_relaxed_v4(&sc->flag[m][g][lane * 4], make_uint4(0, 0, 0, 0));
                fence_gpu();
                __syncwarp();
                if (lane == 0) { st_relaxed_u32(&sc->rdone[m * 8 + g][0], tag); TL(20); }
                const unsigned* rd = &sc->rdone[m * 8 + (lane == 8 && m > 0 ? g - 8 : lane & 7)][0];
                while (!__all_sync(0xffffffffu, ld_relaxed_u32(rd) == tag)) { __nanosleep(POLL_NS); spin_guard(spins); }
                if (lane == 0) { mbar_arrive(bars + BAR_RS * 8); TL(21); }
                unsigned* fo = &sc->flag[m][g][0];
                asm volatile("" : "+l"(fo));
#pragma unroll 1
                for (int t = 0; t < 5; t++) { mbar_wait(bars + (BAR_PA + t) * 8, 0); if (lane == 0) st_relaxed_u32(fo, t + 1); }
                return;
            } else {
                const bool cw = wa < 3, aside = wa >= 5;
                const int l = min(lane, 29), part = l < 24 ? l >> 3 : (l - 24) >> 1;
                const int pp = warp & 1, ri = lane >> 3;
                float s[8];
#pragma unroll
                for (int e = 0; e < 8; e++) s[e] = 0.f;
#define ROW_SUMS(v0, v1, v2) do { _Pragma("unroll") for (int e = 0; e < 4; e++) { \
                    const float wl = bf_lo((&v2.x)[e]), wh = bf_hi((&v2.x)[e]); \
                    const float a = bf_lo((&v0.x)[e]), b = bf_hi((&v0.x)[e]), a2 = bf_lo((&v1.x)[e]), b2 = bf_hi((&v1.x)[e]); \
                    s[0] += a + b; s[1] = fmaf(b, b, fmaf(a, a, s[1])); s[2] = fmaf(b, wh, fmaf(a, wl, s[2])); \
                    s[4] += a2 + b2; s[5] = fmaf(b2, b2, fmaf(a2, a2, s[5])); s[6] = fmaf(b2, wh, fmaf(a2, wl, s[6])); } } while (0)
                if (aside) {
                    const __nv_bfloat16* p0 = x + (m * 128 + g * 16 + 2 * ri + pp) * DM + 384 - k0 + (lane & 7) * 8;
                    const uint32_t wa2 = sb + SM_XSEL + (lane & 7) * 16 + 768 - 2 * k0;
                    cluster_wait();
                    mbar_wait(bars + BAR_WR * 8, 0);
                    if (SIDE_N >= 0) mbar_wait(bars + (BAR_AE + SIDE_N) * 8, 0);
                    uint4 q[4][2];
#pragma unroll
                    for (int j = 0; j < 4; j++) { q[j][0] = ldg_v4(p0 + j * 64); q[j][1] = ldg_v4(p0 + 8 * DM + j * 64); }
                    __syncwarp();
#pragma unroll
                    for (int j = 0; j < 4; j++) { const uint4 wv = lds_v4(wa2 + j * 128); ROW_SUMS(q[j][0], q[j][1], wv); }
                    if (tid == 448) TL(62);
                } else {
                    uint32_t ad[4];
#pragma unroll
                    for (int i = 0; i < 4; i++) {
                        const int row = 4 * ((G & 6) + pp) + i;
                        ad[i] = cw ? OFF_B + rank * B_HALF + (l < 24 ? part * 4096 + row * 128 + (((l ^ row) & 7) << 4) : 12288 + part * 1024 + row * 32 + (((l ^ pp) & 1) << 4))
                                   : (i < 2 ? pp * 8192 + (8 * g + ri + 4 * i) * 128 + (((lane ^ (ri + 4 * i)) & 7) << 4) : SM_XSEL + (lane & 7) * 16 + 2 * k0);
                        ad[i] = __shfl_sync(0xffffffffu, sb + ad[i], lane);
                    }
                    if (wa == 1) st_relaxed_v4(&sc->cs[g][G][rank][lane], make_uint4(tag - 1, 0, 0, 0));
                    cluster_wait();
                    if (ta == 32) mbar_expect_tx(bars + BAR_CX * 8, 2048);
                    mbar_wait(bars + BAR_WR * 8, 0);
#pragma unroll 1
                    for (int kt = 0; kt < (cw ? 5 : 6); kt++) {
                        const uint32_t so = (-kt & 3) * STAGE;
                        mbar_wait(bars + ((cw ? BAR_FULL : BAR_FA) + (kt & 3)) * 8, kt >> 2);
                        const uint4 v0 = lds_v4(ad[0] + so), v1 = lds_v4(ad[1] + so), v2 = lds_v4(ad[2] + (cw ? so : kt * 128 - (kt == 5 ? 4 * k0 : 0)));
                        if (cw) {
                            const uint4 v3 = lds_v4(ad[3] + so);
#pragma unroll
                            for (int e = 0; e < 4; e++) {
                                s[2 * e] += (bf_lo((&v0.x)[e]) + bf_lo((&v1.x)[e])) + (bf_lo((&v2.x)[e]) + bf_lo((&v3.x)[e]));
                                s[2 * e + 1] += (bf_hi((&v0.x)[e]) + bf_hi((&v1.x)[e])) + (bf_hi((&v2.x)[e]) + bf_hi((&v3.x)[e]));
                            }
                        } else ROW_SUMS(v0, v1, v2);
                        __syncwarp();
                        if (lane == 0) mbar_arrive(bars + (BAR_AE + kt) * 8);
                    }
                }
                if (cw) {
                    const uint32_t cx = sb + SM_BX + (rank * 2 + pp) * 512 + lane * 16;
                    st_async_v4(cx, bars + BAR_CX * 8, 0, s[0], s[1], s[2], s[3]); st_async_v4(cx, bars + BAR_CX * 8, 1, s[4], s[5], s[6], s[7]);
                    if (wa == 1) {
                        mbar_wait(bars + BAR_CX * 8, 0);
                        const uint32_t a = sb + SM_BX + lane * 16;
                        const float4 a0 = lds_f4(a), a1 = lds_f4(a + 512), a2 = lds_f4(a + 1024), a3 = lds_f4(a + 1536);
                        st_relaxed_v4(&sc->cs[g][G][rank][lane], make_uint4(tagf((a0.x + a1.x) + (a2.x + a3.x), tag), __float_as_uint((a0.y + a1.y) + (a2.y + a3.y)),
                                                                            __float_as_uint((a0.z + a1.z) + (a2.z + a3.z)), __float_as_uint((a0.w + a1.w) + (a2.w + a3.w))));
                        if (lane == 0) TL(18);
#pragma unroll 1
                        for (int i = lane; i < 140; i += 32) sts_v4(sb + SM_BX + i * 16, make_uint4(0, 0, 0, 0));
                    }
                    bar_sync<7, 64>();
                    uint4 v[8];
#pragma unroll
                    for (int j = 0; j < 8; j++) v[j].x = tag - 1;
                    while (true) {
                        unsigned bad = 0;
#pragma unroll
                        for (int j = 0; j < 8; j++) if ((v[j].x ^ tag) & 15) v[j] = ld_relaxed_v4(&sc->cs[g][j][pp][l]);
                        __syncwarp();
#pragma unroll
                        for (int j = 0; j < 8; j++) bad |= v[j].x ^ tag;
                        if (__all_sync(0xffffffffu, (bad & 15) == 0)) break;
                        spin_guard(spins);
                    }
#pragma unroll
                    for (int e = 0; e < 4; e++) {
                        s[e] = 0.f;
#pragma unroll
                        for (int j = 0; j < 8; j++) s[e] += __uint_as_float((&v[j].x)[e]);
                    }
#pragma unroll
                    for (int j = 0; j < 3; j++) {
                        const int row = 3 * part + j;
                        const uint32_t o0 = pack_bf16(s[0], s[1]), o1 = pack_bf16(s[2], s[3]);
                        s[0] -= bf_lo(o0); s[1] -= bf_hi(o0); s[2] -= bf_lo(o1); s[3] -= bf_hi(o1);
                        sts_f2(sb + SM_BX + pp * 8 + (l < 24 ? row * 128 + (((l ^ row) & 7) << 4) : 1792 + row * 32 + (((l ^ (row >> 2)) & 1) << 4)), __uint_as_float(o0), __uint_as_float(o1));
                    }
                    asm volatile("fence.proxy.async.shared::cta;" ::: "memory");
                    __syncwarp();
                    if (lane == 0) { mbar_arrive(bars + BAR_CS * 8); TL(25); }
                } else {
#pragma unroll
                    for (int e = 0; e < 3; e++) s[e] = ((lane & 4) ? s[4 + e] : s[e]) + shfl_x((lane & 4) ? s[e] : s[4 + e], 4);
#pragma unroll
                    for (int o = 1; o < 4; o <<= 1) {
#pragma unroll
                        for (int e = 0; e < 3; e++) s[e] += shfl_x(s[e], o);
                    }
                    const uint32_t sa = sb + SM_GT + pp * 128 + r * 16;
                    if (aside) {
                        sts_f4(sa, s[0], s[1], s[2], 0.f); asm volatile("bar.arrive 6, 128;" ::: "memory");
                        if (wa == 5) {
                            while (ld_relaxed_u32(&sc->open[g >> 1][0]) != tag) spin_guard(spins);
                            mbar_wait(bars + (BAR_AE + 5) * 8, 0);
                            __nanosleep(MSG_NS);
                            uint4 q[6];
                            while (true) {
#pragma unroll
                                for (int j = 0; j < 6; j++) q[j] = ld_relaxed_v4(&box->msg[min(lane + 32 * j, 160)]);
                                __syncwarp();
                                if (__all_sync(0xffffffffu, max(max(max(q[0].x, q[1].x), max(q[2].x, q[3].x)), max(q[4].x, q[5].x)) != EMPTY_WORD)) break;
                                spin_guard(spins);
                            }
#pragma unroll
                            for (int j = 0; j < 6; j++) sts_v4(sb + SM_XSEL + min(lane + 32 * j, 160) * 16, q[j]);
                            __syncwarp();
                            if (lane == 0) { mbar_arrive(bars + BAR_SEL * 8); TL(23); }
                        }
                    }
                    else {
                        bar_sync<6, 128>();
                        const float4 o = lds_f4(sa);
                        const int row = 8 * g + ri + (lane & 4);
                        const float mean = (s[0] + o.x) * (1.0f / DM);
                        const float sd = sqrt_approx(bfr(bfr(fmaxf(fmaf(-mean, mean, (s[1] + o.y) * (1.0f / DM)), 0.f)) + 1e-5f));
                        if (c == 0) st_relaxed_v2(&sc->rowinfo[m][pp][row], pack_bf16(mean, sd), tagf(s[2] + o.z, tag));
                        if (tid == 384) TL(22);
                    }
                    if (!aside) {
                        const uint4* r0 = reinterpret_cast<const uint4*>(&sc->rowinfo[m][pp][0]);
                        uint4 a, b;
                        while (true) {
                            __nanosleep(POLL_NS);
                            a = ld_relaxed_v4(r0 + lane); b = ld_relaxed_v4(r0 + (m > 0 ? 28 - 64 : 0) + c);
                            if (__all_sync(0xffffffffu, (((a.y ^ tag) | (a.w ^ tag) | (b.y ^ tag) | (b.w ^ tag)) & 15) == 0)) break;
                            spin_guard(spins);
                        }
                        sts_f4(sb + SM_ST + (pp * 72 + 8 + 2 * lane) * 8, bf_lo(a.x), rcp(bf_hi(a.x)), bf_lo(a.z), rcp(bf_hi(a.z)));
                        if (lane < 4) sts_f4(sb + SM_ST + (pp * 72 + 2 * lane) * 8, bf_lo(b.x), rcp(bf_hi(b.x)), bf_lo(b.z), rcp(bf_hi(b.z)));
                        __syncwarp();
                        if (lane == 0) { mbar_arrive(bars + BAR_CS * 8); if (pp == 0) TL(24); }
                    }
                }
            }
            if (wa == 6) {
                const int r = lane >> 1;
                mbar_wait(bars + (BAR_AE + 5) * 8, 0); mbar_wait(bars + (BAR_FA + 2) * 8, 1); mbar_wait(bars + (BAR_EMPTY + 2) * 8, 1);
#pragma unroll 1
                for (int i = 0; i < 8; i++) {
                    const __nv_bfloat16* src = wo + (SRC(i) * 80 + r) * DM + ct + (lane & 1) * 8;
                    const uint32_t dst = sb + SM_WT + (i & 1) * 10240 + r * 128 + ((((i & 6) + (lane & 1)) ^ (r & 7)) << 4);
#pragma unroll
                    for (int t = 0; t < 5; t++) cp_async16(dst + t * 2048, src + t * 16 * DM);
                    __nanosleep(TAIL_NS);
                }
                asm volatile("cp.async.wait_all;\nfence.proxy.async.shared::cta;" ::: "memory");
                __syncwarp();
                if (lane == 0) { mbar_arrive(bars + BAR_WO * 8); TL(19); }
            }
            mbar_wait(bars + BAR_SEL * 8, 0);
            if (moe) {
                const int krow = (lane >> 4) * 8 + (lane & 7), ch = (lane >> 3) & 1;
                const uint32_t wofs = krow * 64 + ((ch ^ (krow >> 1)) & 3) * 16, xa = sb + SM_XSEL + (lane & 1) * 1296 + ch * 16;
                float d[2][4];
#pragma unroll
                for (int e = 0; e < 8; e++) d[e >> 2][e & 3] = 0.f;
                mbar_wait(bars + BAR_GW * 8, 0);
                mbar_wait(bars + (BAR_EMPTY + 1) * 8, 0);
                if (ta == 32) TL(26);
#pragma unroll 1
                for (int ks = wa - 1; ks < 40; ks += 18) {
                    uint32_t a[6][4], b[3][2];
#pragma unroll
                    for (int h = 0; h < 3; h++) {
                        const int k2 = min(ks + 6 * h, 39);
                        const uint32_t wp = sb + (k2 < 35 ? SM_MW : SM_G7 - 35 * 1024) + k2 * 1024 + wofs;
                        ldsm4t(wp, a[2 * h]); ldsm4t(wp ^ 32, a[2 * h + 1]); ldsm2(xa + k2 * 32, b[h][0], b[h][1]);
                    }
                    if (ks > 35) b[1][0] = b[1][1] = b[2][0] = b[2][1] = 0;
#pragma unroll
                    for (int e = 0; e < 6; e++) mma16(d[e & 1], a[e][0], a[e][1], a[e][2], a[e][3], b[e >> 1][0], b[e >> 1][1]);
                }
                if (c == 0) {
#pragma unroll
                    for (int e = 0; e < 4; e++) sts_f2(sb + SM_BX + (wa - 1) * 256 + (e * 8 + r) * 8, d[e >> 1][2 * (e & 1)], d[e >> 1][2 * (e & 1) + 1]);
                }
                bar_sync<3, 192>();
                if (ta == 96) { mbar_arrive(bars + BAR_OE * 8); TL(27); }
                if (wa < 3) {
                    const int t2 = ta - 32;
                    float sum = 0.f;
#pragma unroll
                    for (int e = 0; e < 6; e++) sum += lds_f32(sb + SM_BX + e * 256 + t2 * 4);
                    sum = bfr(sum);
                    st_async_peer(sb + SM_GU + t2 * 4, bars + BAR_PX * 8, rank ^ 1, __float_as_uint(sum));
                    mbar_wait(bars + BAR_PX * 8, 0);
                    const float oth = lds_f32(sb + SM_GU + t2 * 4), gs = rank ? oth : sum, us = rank ? sum : oth;
                    sts_u16(sb + SM_H + (t2 & 1) * 64 + (t2 >> 1) * 2, pack_bf16(bfr(gs * sigmoid_f(gs)) * us, 0.f));
                }
                mbar_wait(bars + BAR_DW * 8, 0);
                bar_sync<3, 192>();
                if (wa >= 3) {
                    uint32_t hb[4];
                    ldsm4(sb + SM_H + (lane & 1) * 64 + (lane >> 3) * 16, hb[0], hb[1], hb[2], hb[3]);
                    float yv[5];
#pragma unroll
                    for (int b = 0; b < 5; b++) {
                        const int nb = (wa - 3) * 5 + b;
                        const uint32_t wp = sb + SM_DW + (nb >> 2) * 4096 + krow * 128 + ((((nb & 3) * 2 + ch) ^ (krow & 7)) << 4);
                        uint32_t a0[4], a1[4];
                        ldsm4t(wp, a0); ldsm4t(wp + 2048, a1);
                        float o[4] = {0.f, 0.f, 0.f, 0.f};
                        mma16(o, a0[0], a0[1], a0[2], a0[3], hb[0], hb[1]); mma16(o, a1[0], a1[1], a1[2], a1[3], hb[2], hb[3]);
                        yv[b] = (c & 2) ? ((c & 1) ? o[3] : o[2]) : ((c & 1) ? o[1] : o[0]);
                    }
                    uint4* const dst = &sc->yp[rank * 4 + wa - 3][mi][0];
                    st_relaxed_v4(dst + lane, make_uint4(tagf(yv[0], tag), __float_as_uint(yv[1]), __float_as_uint(yv[2]), __float_as_uint(yv[3])));
                    st_relaxed_u32(reinterpret_cast<unsigned*>(dst + 32) + lane, tagf(yv[4], tag));
                    bar_sync<7, 128>();
                    if (tid == 384) { mbar_arrive(bars + (BAR_OE + 1) * 8); TL(28); }
                }
            } else if (ta == 32) { mbar_arrive(bars + BAR_OE * 8); mbar_arrive(bars + (BAR_OE + 1) * 8); }
            if (wa == 2) {
                const uint2 sel = lds_v2(sb + SM_TOP);
                if ((sel.x >> 7) == m || (sel.y >> 7) == m) {
                    uint4 v;
                    do { __nanosleep(POLL_NS); v = ld_relaxed_v4(&box->gt[g & 1][min(lane, 19)]); spin_guard(spins); } while (__any_sync(0xffffffffu, v.x == EMPTY_WORD));
                    sts_v4(sb + SM_GT + min(lane, 19) * 16, v);
                    __syncwarp();
                    if (lane == 0) TL(30);
                }
                if (lane == 0) { mbar_arrive(bars + BAR_Y * 8); st_relaxed_u32(&sc->epoch[cta * 32], tag); }
            }
        }
    } else {
        asm volatile("setmaxnreg.inc.sync.aligned.u32 192;");
        const int p = warp >> 2, w = warp & 3, c = lane & 3, r = lane >> 2;
        const uint32_t stb = sb + SM_ST + (p * 72 + w * 16) * 8;
        float acc[120];
#pragma unroll
        for (int i = 0; i < 120; i++) asm volatile("" : "=f"(acc[i]));
        uint32_t xs[5][4];
#pragma unroll
        for (int i = 0; i < 20; i++) asm volatile("" : "=r"(xs[i >> 2][i & 3]));
        cluster_wait();
        {
            const int lr = w * 16 + (lane & 15);
            uint32_t st = __shfl_sync(0xffffffffu, sb + p * 8192 + lr * 128 + (((lr & 7) ^ (lane >> 4)) << 4), lane);
            const bool lead = __shfl_sync(0xffffffffu, tid & 127, lane) == 0;
            uint32_t blo = (((sb + OFF_B) & 0x3ffffu) >> 4) | ((4096u >> 4) << 16);
            const uint32_t tdiff = (12288u >> 4) + ((1024u >> 4) << 16) - ((4096u >> 4) << 16);
            const int kx = (5 * g) >> 2;
#define PD 1
            uint32_t af[4][4];
            mbar_wait(bars + BAR_FA * 8, 0);
            ldsm4(st, af[0][0], af[0][1], af[0][2], af[0][3]);
            if (PD == 2) ldsm4(st ^ 32, af[1][0], af[1][1], af[1][2], af[1][3]);
#pragma unroll 1
            for (int kt = 0; kt < 10; kt++) {
#pragma unroll
                for (int j = 0; j < 4; j++) {
                    uint32_t (&nx)[4] = af[(j + PD) & 3];
                    if (j == 0) {
                        mbar_wait(bars + (BAR_FULL + (kt & 3)) * 8, (kt >> 2) & 1);
                    }
                    if (j == 4 - PD && kt < 9) {
                        st += (kt & 3) == 0 ? 3 * STAGE : -STAGE;
                        mbar_wait(bars + (BAR_FA + ((kt + 1) & 3)) * 8, ((kt + 1) >> 2) & 1);
                    }
                    ldsm4(st ^ (((j + PD) & 3) << 5), nx[0], nx[1], nx[2], nx[3]);
                    wg_fence();
                    const uint32_t sd = j ? 1u : (uint32_t)kt;
                    wgmma_rs_n48(acc, af[j][0], af[j][1], af[j][2], af[j][3], blo + tdiff + (j >> 1) * (B_HALF >> 4) + (j & 1) * 32, sd);
                    wgmma_rs_n192(acc, af[j][0], af[j][1], af[j][2], af[j][3], blo + (j >> 1) * (B_HALF >> 4) + (j & 1) * 128, sd);
                    wg_commit();
#define WD 2
                    wg_wait<WD>();
                    if (j == WD - 1 && kt > 0 && lead) mbar_arrive_both(bars + (BAR_EMPTY + ((kt - 1) & 3)) * 8);
                    const int kg = kt + ((kt < 5 ? k0 : -k0) >> 6);
                    if (j == 1 && (unsigned)(kg - kx) < 2u) {
#pragma unroll
                        for (int t = 0; t < 5; t++) {
                            const int ks = 5 * g + (t < 4 ? t + odd : 4 - 4 * odd);
                            ldsm4_if((ks >> 2) == kg, st ^ ((ks & 3) << 5), xs[t]);
                        }
                    }
                }
                blo += (kt & 3) == 0 ? 3 * (STAGE >> 4) : -(STAGE >> 4);
            }
        }
        mbar_wait(bars + BAR_CS * 8, 0);
        if (tid == 0) TL(10);
        const float2 st0 = lds_f2(stb + (8 + r) * 8), st1 = lds_f2(stb + (16 + r) * 8);
        {
            const uint32_t msk = c == 0 ? 0xffffffffu : (c == 1 ? 0x0000ffffu : 0u);
            const uint32_t e0 = dup_hi(-st0.x) & msk, e1 = dup_hi(-st1.x) & msk;
            wg_fence();
            wgmma_rs_n48x(acc, e0, e1, 0u, 0u, (((sb + SM_BX + 1792) & 0x3ffffu) >> 4) | ((96u >> 4) << 16));
            wgmma_rs_n192x(acc, e0, e1, 0u, 0u, (((sb + SM_BX) & 0x3ffffu) >> 4) | ((384u >> 4) << 16));
            wg_commit();
        }
        const float rs0 = st0.y, rs1 = st1.y;
        const uint4 sP = lds_v4(stb + (2 * c) * 8), sB = lds_v4(stb + (8 + 2 * c) * 8), sC = lds_v4(stb + (16 + 2 * c) * 8);
        const bool up0 = 2 * c > r, up1 = 2 * c + 1 > r;
        const float k00 = __uint_as_float(up0 ? sP.y : sB.y), k01 = __uint_as_float(up1 ? sP.w : sB.w);
        const float k10 = __uint_as_float(up0 ? sB.y : sC.y), k11 = __uint_as_float(up1 ? sB.w : sC.w);
        const float sc2 = 0.22360679774997896f * 1.4426950408889634f;
        const float f00 = rs0 * k00 * sc2, f01 = rs0 * k01 * sc2, f10 = rs1 * k10 * sc2, f11 = rs1 * k11 * sc2;
        const float fa[4] = {up0 ? f00 : 0.f, up1 ? f01 : 0.f, up0 ? f10 : 0.f, up1 ? f11 : 0.f};
        const float fb[4] = {f00 - fa[0], f01 - fa[1], f10 - fa[2], f11 - fa[3]};
        const bool first = (m == 0 && w == 0);
        const float b00 = (first && up0) ? -1e30f : 0.f, b01 = (first && up1) ? -1e30f : 0.f;
#define PV3 0
#define MSK(a, b) ((a) & (b))
        const uint32_t mup = (up0 ? 0x0000ffffu : 0u) | (up1 ? 0xffff0000u : 0u), mdn = ~mup;
        const uint32_t qlo = c < 2;
        const uint32_t exs = sb + SM_EX + p * 8192 + w * 2560 + lane * 16;
        const uint32_t exr = __shfl_sync(0xffffffffu, exs - (w ? 2560 : 0), lane);
        uint4* hg = &sc->halo[m * 8 + g - (w ? 0 : 8)][p * 160 + lane];
        uint32_t* ob = reinterpret_cast<uint32_t*>(&sc->o[m][0][g][warp * 32]) + lane;
        asm volatile("" : "+l"(hg), "+l"(ob));
        mbar_wait(bars + BAR_RS * 8, 0);
        if (p == 0) bar_sync<1, 128>(); else bar_sync<2, 128>();
        wg_wait<0>();
        if ((tid & 127) == 0) { mbar_arrive_both(bars + (BAR_EMPTY + 1) * 8); TL(2 + p); }
        uint32_t Q[10][2], K[10][2], V[10][2], Kp[10], Vp[10];
        if (odd) pack_kv<1, 1>(acc, K, V); else pack_kv<0, 1>(acc, K, V);
        ATS(0);
        uint4 rcv[5];
        {
            const uint4 snd[5] = {make_uint4(K[0][1], K[1][1], K[3][1], K[4][1]), make_uint4(K[5][1], K[6][1], K[8][1], K[9][1]), make_uint4(K[2][1], K[7][1], V[0][1], V[1][1]),
                                  make_uint4(V[2][1], V[3][1], V[4][1], V[5][1]), make_uint4(V[6][1], V[7][1], V[8][1], V[9][1])};
            if (w == 3) {
#pragma unroll
                for (int i = 0; i < 5; i++) st_relaxed_v4(hg + i * 32, snd[i]);
            } else {
#pragma unroll
                for (int i = 0; i < 5; i++) sts_v4(exs + i * 512, snd[i]);
            }
            if (tid == 96) TL(11);
        }
        ATS(2);
#define BX(h) (5 * ((h) >> 1) + 3 * ((h) & 1))
#define BZ(h) (5 * ((h) >> 1) + 2)
        float l[4][2];
        uint32_t qz[4][2], pa[4][4];
#define PROBS(la, lb, h, ka, kb, iu, id) do { \
            const float e0 = ex2(la[0]), e1 = ex2(la[1]), e2 = ex2(lb[0]), e3 = ex2(lb[1]); \
            float sum[4] = {0.f, 0.f, 0.f, 0.f}; \
            mma8(sum, pack_bf16(e0, e1), pack_bf16(e2, e3), 0x3f803f80u); \
            const float i0 = rcp(sum[0]), i1 = rcp(sum[2]); \
            const uint32_t p0 = pack_bf16(e0 * ka * i0, e1 * kb * i0), p1 = pack_bf16(e2 * ka * i1, e3 * kb * i1); \
            pa[h][iu] = MSK(p0, mup); pa[h][id] = MSK(p0, mdn); pa[(h) + 1][iu] = MSK(p1, mup); pa[(h) + 1][id] = MSK(p1, mdn); } while (0)
        float lu[4][2];
#define OWN_KEYS(ODD) do { pack_q<ODD>(acc, Q); pack_kv<ODD, 0>(acc, K, V); \
            _Pragma("unroll") for (int h = 0; h < 4; h++) { \
                const int bx = BX(h), by = bx + 1, bz = BZ(h); \
                if (h & 1) { qz[h][0] = Q[bz][0] - qz[h & 2][0]; qz[h][1] = Q[bz][1] - qz[h & 2][1]; } \
                else { qz[h][0] = imul(Q[bz][0], qlo); qz[h][1] = imul(Q[bz][1], qlo); } \
                float sm_[4] = {0.f, 0.f, 0.f, 0.f}, sn[4] = {0.f, 0.f, 0.f, 0.f}; \
                mma16(sm_, Q[bx][0], Q[bx][1], Q[by][0], Q[by][1], K[bx][0], K[by][0]); \
                mma16(sn, Q[bx][0], Q[bx][1], Q[by][0], Q[by][1], K[bx][1], K[by][1]); \
                mma8(sm_, qz[h][0], qz[h][1], K[bz][0]); mma8(sn, qz[h][0], qz[h][1], K[bz][1]); \
                l[h][0] = fmaf(sm_[0], fb[0], b00); l[h][1] = fmaf(sm_[1], fb[1], b01); \
                lu[h][0] = fmaf(sm_[2], fa[2], sn[2] * fb[2]); lu[h][1] = fmaf(sm_[3], fa[3], sn[3] * fb[3]); \
                asm volatile("" : "+f"(lu[h][0]), "+f"(lu[h][1]) :: "memory"); \
            } } while (0)
        if (odd) OWN_KEYS(1); else OWN_KEYS(0);
        ATS(1);
        if (p == 0) bar_sync<1, 128>(); else bar_sync<2, 128>();
        if (w == 0 && m > 0) {
#pragma unroll
            for (int i = 0; i < 5; i++) rcv[i] = ld_relaxed_v4(hg + i * 32);
        } else {
#pragma unroll
            for (int i = 0; i < 5; i++) rcv[i] = lds_v4(exr + i * 512);
        }
#pragma unroll
        for (int h = 0; h < 4; h++) {
            float m1 = fmaxf(lu[h][0], lu[h][1]);
            m1 = fmaxf(m1, shfl_x(m1, 1)); m1 = fmaxf(m1, shfl_x(m1, 2));
            lu[h][0] -= m1; lu[h][1] -= m1;
        }
        PROBS(lu[0], lu[1], 0, k10, k11, 1, 3); PROBS(lu[2], lu[3], 2, k10, k11, 1, 3);
#pragma unroll
        for (int h = 0; h < 4; h++) asm volatile("" : "+r"(pa[h][1]), "+r"(pa[h][3]) :: "memory");
        ATS(3);
        if (w == 0 && m > 0) {
            unsigned spins = 0;
            while (__any_sync(0xffffffffu, max(max(max(rcv[0].x, rcv[1].x), max(rcv[2].x, rcv[3].x)), rcv[4].x) == EMPTY_WORD) && ++spins < SPIN_MAX) {
#pragma unroll
                for (int i = 0; i < 5; i++) rcv[i] = ld_relaxed_v4(hg + i * 32);
            }
        }
        Kp[0] = rcv[0].x; Kp[1] = rcv[0].y; Kp[3] = rcv[0].z; Kp[4] = rcv[0].w; Kp[5] = rcv[1].x; Kp[6] = rcv[1].y; Kp[8] = rcv[1].z; Kp[9] = rcv[1].w;
        Kp[2] = rcv[2].x; Kp[7] = rcv[2].y; Vp[0] = rcv[2].z; Vp[1] = rcv[2].w; Vp[2] = rcv[3].x; Vp[3] = rcv[3].y; Vp[4] = rcv[3].z; Vp[5] = rcv[3].w;
        Vp[6] = rcv[4].x; Vp[7] = rcv[4].y; Vp[8] = rcv[4].z; Vp[9] = rcv[4].w;
        ATS(4);
        if (tid == 0) TL(4);
        if (tid == 32) TL(5);
        uint32_t of[10][2];
#define PUBLISH(t) do { st_relaxed_u32(ob + (t) * 8192, of[2 * (t)][0]); st_relaxed_u32(ob + (t) * 8192 + 32, of[2 * (t) + 1][0]); \
            st_relaxed_u32(ob + (t) * 8192 + 64, of[2 * (t)][1]); st_relaxed_u32(ob + (t) * 8192 + 96, of[2 * (t) + 1][1]); \
            if (lane == 0) mbar_arrive(bars + (BAR_PA + (t)) * 8); } while (0)
#define FRONT(h) do { \
            float sp[4] = {0.f, 0.f, 0.f, 0.f}; \
            mma16(sp, Q[BX(h)][0], Q[BX(h)][1], Q[BX(h) + 1][0], Q[BX(h) + 1][1], Kp[BX(h)], Kp[BX(h) + 1]); \
            mma8(sp, qz[h][0], qz[h][1], Kp[BZ(h)]); \
            l[h][0] = fmaf(sp[0], fa[0], l[h][0]); l[h][1] = fmaf(sp[1], fa[1], l[h][1]); \
            float m0 = fmaxf(l[h][0], l[h][1]); \
            m0 = fmaxf(m0, shfl_x(m0, 1)); m0 = fmaxf(m0, shfl_x(m0, 2)); \
            l[h][0] -= m0; l[h][1] -= m0; } while (0)
#define MID(h) PROBS(l[h], l[(h) + 1], h, k00, k01, 2, 0)
#define BACK(h) do { \
            _Pragma("unroll") for (int b = 0; b < 3; b++) { \
                const int bb = b < 2 ? BX(h) + b : BZ(h); \
                float O[4] = {0.f, 0.f, 0.f, 0.f}; \
                if (PV3) { mma8(O, 0u, pa[h][3], V[bb][1]); mma8(O, pa[h][0], pa[h][1], V[bb][0]); } \
                else mma16(O, pa[h][0], pa[h][1], 0u, pa[h][3], V[bb][0], V[bb][1]); \
                mma8(O, pa[h][2], 0u, Vp[bb]); \
                const uint32_t o0 = pack_bf16(O[0], O[1]), o1 = pack_bf16(O[2], O[3]); \
                of[bb][0] = (b == 2 && ((h) & 1) && c < 2) ? of[bb][0] : o0; of[bb][1] = (b == 2 && ((h) & 1) && c < 2) ? of[bb][1] : o1; \
            } } while (0)
#define HOLD_L(h) asm volatile("" : "+f"(l[h][0]), "+f"(l[h][1]) :: "memory")
#define HOLD_K(h) asm volatile("" : "+r"(Kp[BX(h)]) :: "memory")
#define PA() do { if (tid == 0) TL(6); if (tid == 32) TL(8); } while (0)
#define HOLD_P(h) asm volatile("" : "+r"(pa[h][0]), "+r"(pa[h][2]), "+r"(pa[h][3]) :: "memory")
        FRONT(0); FRONT(1); MID(0); BACK(0); PUBLISH(0); PA(); sched_fence(); HOLD_P(1); HOLD_K(2); HOLD_K(3); FRONT(2); FRONT(3); BACK(1); PUBLISH(1); MID(2); BACK(2); PUBLISH(2); BACK(3);
        if (tid == 0) TL(7);
        if (tid == 32) TL(9);
#define TRK 4
        float acc2[40];
#pragma unroll
        for (int i = 0; i < 40; i++) asm volatile("" : "=f"(acc2[i]));
        uint32_t gate[5][4];
        if ((TRK <= 1 || TRK == 4) && SPLIT != 3) PUBLISH(2);
        if (TRK == 0) { PUBLISH(3); PUBLISH(4); }
        const float2 su0 = lds_f2(stb + (8 + r) * 8), su1 = lds_f2(stb + (16 + r) * 8);
        const float rh0 = bfr(0.5f * su0.y), rh1 = bfr(0.5f * su1.y);
        const uint32_t gm[2] = {dup_hi(su0.x), dup_hi(su1.x)}, gh[2] = {dup_hi(rh0), dup_hi(rh1)};
        const uint32_t gl[2] = {pack_bf16(0.5f * su0.y - rh0, 0.5f * su0.y - rh0), pack_bf16(0.5f * su1.y - rh1, 0.5f * su1.y - rh1)};
        mbar_wait(bars + BAR_WO * 8, 0);
        bar_sync<4, 256>();
        if (tid == 0) TL(13);
        const uint32_t wlo = ((sb + SM_WO) & 0x3ffffu) >> 4, alo = (((sb + p * 2048) & 0x3ffffu) >> 4) | (8u << 16);
#define WPOS(ks) ((7 - (ks) / 5) * 5 + (ks) % 5)
#define WDESC(ks) (wlo + WPOS(ks) * 128 + (((SM_WT - SM_WO + ((ks) % 10 - WPOS(ks)) * 2048 + ((ks) / 10) * 32) >> 4) << 16))
        wg_fence();
#pragma unroll
        for (int t = 0; t < 5; t++) wgmma_rs_n80(acc2, of[2 * t][0], of[2 * t][1], of[2 * t + 1][0], of[2 * t + 1][1], WDESC(t), t != 0);
        wg_commit();
#define NG0 2
#define GATES(t) do { _Pragma("unroll") for (int e = 0; e < 4; e++) {        \
                const uint32_t d = hsub2(xs[t][e], gm[e & 1]), h2 = hfma2(d, gh[e & 1], hmul2(d, gl[e & 1]));        \
                const float a = bf_lo(h2), b = bf_hi(h2); \
                gate[t][e] = pack_bf16(fmaf(a, tanh_f(a), a), fmaf(b, tanh_f(b), b)); \
                asm volatile("" : "+r"(gate[t][e]) :: "memory"); } } while (0)
        GATES(0);
        if (TRK == 4) { sched_fence(); PUBLISH(3); }
        if (TRK && TRK < 4) {
            mbar_wait(bars + BAR_GI * 8, 0);
            if (TRK >= 2 && SPLIT != 3) PUBLISH(2);
            if (TRK <= 2) { PUBLISH(3); PUBLISH(4); }
        }
#pragma unroll
        for (int t = 1; t < NG0; t++) GATES(t);
        if (TRK == 4) { sched_fence(); PUBLISH(4); }
        if (tid == 0) TL(12);
#pragma unroll
        for (int t = 0; t < 5; t++) {
            const uint32_t ad = alo + ((t == 2 ? SM_O2 : ((t == 0 || t == 3) ? SM_O0 : SM_O1)) >> 4);
            mbar_wait(bars + (BAR_OF + t) * 8, 0);
            if (STAG < 5 && t == STAG && p == 1) bar_sync<5, 256>();
            if (TRK == 3 && t == 0) { PUBLISH(3); PUBLISH(4); }
            wg_fence();
#pragma unroll
            for (int i = 0; i < 7; i++) {
                wgmma_ss_n80(acc2, ad + i * 256, WDESC((i + 1) * 5) + t * 128);
                if (i == 0 && (t == 1 || t == 2)) {
                    wg_commit(); wg_wait<1>();
                    if ((tid & 127) == 0) mbar_arrive(bars + (BAR_OE + t + 1) * 8);
                }
                if (STAG < 5 && i == 4 && t == 4 && p == 0) asm volatile("bar.arrive 5, 256;" ::: "memory");
            }
            wg_commit();
            if (t + NG0 < 5) GATES(t + NG0);
        }
        const int wrow = m * 128 + 32 * w + p;
        {
            mbar_wait(bars + BAR_SEL * 8, 0);
            const uint2 sel = lds_v2(sb + SM_TOP);
            const unsigned d0 = sel.x - wrow, d1 = sel.y - wrow;
            if ((d0 & ~30u) == 0 || (d1 & ~30u) == 0) {
                mbar_wait(bars + BAR_Y * 8, 0);
#pragma unroll
                for (int h = 0; h < 2; h++) {
                    const unsigned me = 2 * r + 16 * h;
                    if (d0 == me || d1 == me) {
#pragma unroll
                        for (int t = 0; t < 5; t++) {
                            const uint32_t a = sb + SM_GT + (d0 == me ? 0 : 160) + (t < 4 ? t + odd : 4 - 4 * odd) * 32 + c * 4;
                            gate[t][h] = lds_u32(a); gate[t][2 + h] = lds_u32(a + 16);
                        }
                    }
                }
                __syncwarp();
            }
        }
        const uint32_t ssb = sb + (warp < 6 ? SM_EX : SM_G7 - 6 * 2560) + warp * 2560;
        const uint32_t laddr = ssb + (lane & 15) * 160 + (lane >> 4) * 16;
        wg_wait<0>();
        if (tid == 0) TL(1);
        if (tid == 128) TL(14);
        if (__any_sync(0xffffffffu, acc2[0] != acc2[0] || acc2[2] != acc2[2])) {
#pragma unroll
            for (int i = 0; i < 40; i++) acc2[i] = 0.f;
            const int krow = lane & 15;
#pragma unroll 1
            for (int ks = 0; ks < 40; ks++) {
                const int i = ks / 5;
                const uint32_t* src = ob + (ks - 5 * i) * 8192 + (SRC(i) - g) * 1024;
                uint32_t a0, a1, a2, a3; unsigned spins = 0;
                do { a0 = ld_relaxed_u32(src); a2 = ld_relaxed_u32(src + 32); a1 = ld_relaxed_u32(src + 64); a3 = ld_relaxed_u32(src + 96); }
                while (__any_sync(0xffffffffu, max(max(a0, a1), max(a2, a3)) == EMPTY_WORD) && ++spins < SPIN_MAX);
#pragma unroll
                for (int nb = 0; nb < 5; nb++) {
                    uint32_t b[4];
                    ldsm4t(sb + (nb < 4 ? SM_WO + (35 + ks - 10 * i) * 2048 : SM_WT + (ks % 10) * 2048) + krow * 128 + (((2 * (nb < 4 ? nb : ks / 10) + (lane >> 4)) ^ (krow & 7)) << 4), b);
                    mma16(*reinterpret_cast<float (*)[4]>(&acc2[8 * nb]), a0, a1, a2, a3, b[0], b[1]);
                    mma16(*reinterpret_cast<float (*)[4]>(&acc2[8 * nb + 4]), a0, a1, a2, a3, b[2], b[3]);
                }
            }
        }
#pragma unroll
        for (int t = 0; t < 5; t++) {
            uint32_t o[4];
#pragma unroll
            for (int e = 0; e < 4; e++) o[e] = hadd2(xs[t][e], hmul2(pack_bf16(acc2[8 * t + 2 * e], acc2[8 * t + 2 * e + 1]), gate[t][e]));
            stsm4(laddr + (t < 4 ? t + odd : 4 - 4 * odd) * 32, o[0], o[1], o[2], o[3]);
        }
        asm volatile("fence.proxy.async.shared::cta;" ::: "memory");
        __syncwarp();
        if (elect_one()) tma3d_store(&tm_o, ssb, g * 80, m * 64 + w * 16, p);
    }
}

typedef CUresult (*EncodeFn)(CUtensorMap*, CUtensorMapDataType, cuuint32_t, void*, const cuuint64_t*, const cuuint64_t*, const cuuint32_t*,
                             const cuuint32_t*, CUtensorMapInterleave, CUtensorMapSwizzle, CUtensorMapL2promotion, CUtensorMapFloatOOBfill);

static void encode(EncodeFn enc, CUtensorMap* tm, const void* ptr, int rank, uint64_t d0, uint64_t d1, uint64_t d2, uint64_t s1, uint64_t s2,
                   uint32_t b0, uint32_t b1, uint32_t b2, CUtensorMapSwizzle swz) {
    cuuint64_t dims[3] = {d0, d1, d2}, strides[2] = {s1, s2};
    cuuint32_t box[3] = {b0, b1, b2}, es[3] = {1, 1, 1};
    enc(tm, CU_TENSOR_MAP_DATA_TYPE_BFLOAT16, rank, const_cast<void*>(ptr), dims, strides, box, es, CU_TENSOR_MAP_INTERLEAVE_NONE, swz,
        CU_TENSOR_MAP_L2_PROMOTION_L2_128B, CU_TENSOR_MAP_FLOAT_OOB_FILL_NONE);
}

}

extern "C" void kernel_launch(void* const* d_in, const int* in_sizes, int n_in, void* d_out, int out_size) {
    using namespace fk;
    (void)in_sizes; (void)n_in; (void)out_size;
    const __nv_bfloat16* x = (const __nv_bfloat16*)d_in[0];
    const __nv_bfloat16* wqkv = (const __nv_bfloat16*)d_in[1];
    const __nv_bfloat16* wo = (const __nv_bfloat16*)d_in[2];
    const __nv_bfloat16* wr = (const __nv_bfloat16*)d_in[4];
    const __nv_bfloat16* wg = (const __nv_bfloat16*)d_in[5];
    const __nv_bfloat16* wu = (const __nv_bfloat16*)d_in[6];
    const __nv_bfloat16* wd = (const __nv_bfloat16*)d_in[7];
    static EncodeFn enc = nullptr;
    static Scratch* scratch = nullptr;
    static Roles roles; static int by_sm = 0;
    if (!enc) {
        void* fn = nullptr; cudaDriverEntryPointQueryResult qr;
        cudaGetDriverEntryPoint("cuTensorMapEncodeTiled", &fn, cudaEnableDefault, &qr);
        enc = (EncodeFn)fn;
        cudaFuncSetAttribute(fused_kernel, cudaFuncAttributeMaxDynamicSharedMemorySize, SM_TOTAL);
        cudaGetSymbolAddress((void**)&scratch, g_scratch);
        int dev = 0, nsm = 0;
        cudaGetDevice(&dev); cudaDeviceGetAttribute(&nsm, cudaDevAttrMultiProcessorCount, dev);
        by_sm = nsm == NCTA + NIDLE;
        for (int t = 0; t < 66; t++) roles.pair[t] = t < 32 ? (t & 7) * 8 + (t >> 3) : (t < 60 ? (1 + (t - 32) % 7) * 8 + 4 + (t - 32) / 7 : (t < 62 ? t + 4 : t - 58));
    }
    CUtensorMap tx, tw, twt, two, td, tg, tu, to;
    encode(enc, &tx, x, 3, 640, 1024, 2, 2560, 1280, 64, 64, 2, CU_TENSOR_MAP_SWIZZLE_128B);
    encode(enc, &tw, wqkv, 3, 640, 640, 3, 3840, 1280, 64, 32, 3, CU_TENSOR_MAP_SWIZZLE_128B);
    encode(enc, &twt, wqkv, 3, 640, 640, 3, 3840, 1280, 16, 32, 3, CU_TENSOR_MAP_SWIZZLE_32B);
    encode(enc, &two, wo, 2, 640, 640, 1, 1280, 0, 64, 80, 1, CU_TENSOR_MAP_SWIZZLE_128B);
    encode(enc, &td, wd, 2, 640, 1728, 1, 1280, 0, 64, 32, 1, CU_TENSOR_MAP_SWIZZLE_128B);
    encode(enc, &to, d_out, 3, 640, 1024, 2, 2560, 1280, 80, 16, 1, CU_TENSOR_MAP_SWIZZLE_NONE);
    encode(enc, &tg, wg, 2, 1728, 640, 1, 3456, 0, 32, 80, 1, CU_TENSOR_MAP_SWIZZLE_64B);
    encode(enc, &tu, wu, 2, 1728, 640, 1, 3456, 0, 32, 80, 1, CU_TENSOR_MAP_SWIZZLE_64B);
    fused_kernel<<<NCTA + NIDLE, NTHREADS, SM_TOTAL>>>(scratch, x, wqkv, wo, wr, wd, (__nv_bfloat16*)d_out, by_sm, roles, tx, tw, twt, two, td, tg, tu, to);
}
```

```cpp
#include <cuda_runtime.h>
#include <cuda_bf16.h>
#include <cuda.h>
#include <stdint.h>

#define DEVI __device__ __forceinline__

namespace fk {

constexpr int DM = 640;
constexpr int NCTA = 128, NIDLE = 4, NTHREADS = 512;
constexpr int NMOE = 54;
constexpr int STAGE = 47104;
constexpr int OFF_B = 16384, B_HALF = 15360;
constexpr int SM_DW = 0;
constexpr int SM_WO = 33792;
constexpr int SM_G7 = SM_WO + 81920;
constexpr int SM_WT = SM_G7 + 5120;
constexpr int SM_EX = 3 * STAGE;
constexpr int SM_O0 = 3 * STAGE + OFF_B, SM_O1 = 4 * STAGE, SM_O2 = SM_DW;
constexpr int SM_MW = 4 * STAGE;
constexpr int SM_BX = SM_MW + 35840;
constexpr int SM_XSEL = SM_BX + 2560;
constexpr int SM_ST = SM_XSEL + 2592;
constexpr int SM_GT = SM_ST + 1152;
constexpr int SM_H = SM_GT + 320;
constexpr int SM_TOP = SM_XSEL + 1280;
constexpr int SM_BAR = SM_H + 128;
constexpr int SM_TL = SM_BAR + 352;
constexpr int SM_TOTAL = SM_TL;
static_assert(SM_TOTAL <= 232448 && SM_BAR % 8 == 0 && SM_XSEL % 16 == 0 && SM_ST % 16 == 0 && SM_GT % 16 == 0 && SM_BX % 1024 == 0 && SM_TOP % 16 == 0, "smem layout");
constexpr int BAR_FULL = 0, BAR_EMPTY = 4, BAR_WR = 8, BAR_Y = 9, BAR_GW = 10, BAR_DW = 11, BAR_PX = 12, BAR_RS = 13, BAR_SEL = 14, BAR_GI = 15, BAR_CX = 42,
              BAR_OF = 16  , BAR_OE = 21  , BAR_WO = 25, BAR_CS = 26, BAR_PA = 27  , BAR_AE = 32  , BAR_FA = 38  , NBAR = 43;
#define POLL_NS 100
#define PF1_NS 200
#define STAG 3
#define GP0 3
#define DP0 99
constexpr uint32_t EMPTY_WORD = 0xffffffffu;
struct Roles { unsigned k16; unsigned short pair[NCTA / 2 + NIDLE / 2]; };
constexpr unsigned SPIN_MAX = 1u << 20;

struct Outbox {
    uint4 msg[192];
    uint4 gt[2][32];
};
struct Scratch {
    uint4 o[16][5][8][256];
    uint4 halo[NCTA][320];
    unsigned flag[16][8][8];
    Outbox box[NIDLE];
    uint4 cs[8][8][2][32];
    uint4 yp[8][56][40];
    uint2 rowinfo[16][2][64];
    unsigned rdone[NCTA][8];
    unsigned open[NIDLE][32];
    unsigned epoch[(NCTA + NIDLE) * 32];
};
__device__ Scratch g_scratch;
#define TL(i) do { } while (0)

DEVI uint32_t smem_u32(const void* p) { return (uint32_t)__cvta_generic_to_shared(p); }
DEVI void mbar_init(uint32_t bar, uint32_t cnt) { asm volatile("mbarrier.init.shared::cta.b64 [%0], %1;" :: "r"(bar), "r"(cnt)); }
DEVI void mbar_expect_tx(uint32_t bar, uint32_t bytes) { asm volatile("mbarrier.arrive.expect_tx.shared::cta.b64 _, [%0], %1;" :: "r"(bar), "r"(bytes) : "memory"); }
DEVI void mbar_arrive(uint32_t bar) { asm volatile("mbarrier.arrive.shared::cta.b64 _, [%0];" :: "r"(bar) : "memory"); }
DEVI uint32_t clk32() { uint32_t t; asm volatile("mov.u32 %0, %%clock;" : "=r"(t) :: "memory"); return t; }
DEVI void sched_fence() { asm volatile("pmevent 0;" ::: "memory"); }
DEVI bool mbar_try(uint32_t bar, uint32_t parity) {
    uint32_t ok;
    asm volatile("{\n.reg .pred p;\nmbarrier.try_wait.parity.shared::cta.b64 p, [%1], %2, 0x989680;\nselp.u32 %0, 1, 0, p;\n}" : "=r"(ok) : "r"(bar), "r"(parity) : "memory");
    return ok != 0;
}
DEVI void mbar_wait(uint32_t bar, uint32_t parity) {
    while (!mbar_try(bar, parity)) { }
}
DEVI void mbar_spin(uint32_t bar, uint32_t parity) {
    uint32_t ok;
    do { asm volatile("{\n.reg .pred p;\nmbarrier.try_wait.parity.shared::cta.b64 p, [%1], %2;\nselp.u32 %0, 1, 0, p;\n}" : "=r"(ok) : "r"(bar), "r"(parity) : "memory"); } while (!ok);
}
DEVI bool elect_one() {
    uint32_t p;
    asm volatile("{\n.reg .pred P;\nelect.sync _|P, 0xffffffff;\nselp.u32 %0, 1, 0, P;\n}" : "=r"(p));
    return p != 0;
}
DEVI void tma3d(uint32_t dst, const CUtensorMap* tm, uint32_t bar, int c0, int c1, int c2) {
    asm volatile("cp.async.bulk.tensor.3d.shared::cluster.global.mbarrier::complete_tx::bytes [%0], [%1, {%3, %4, %5}], [%2];"
                 :: "r"(dst), "l"(tm), "r"(bar), "r"(c0), "r"(c1), "r"(c2) : "memory");
}
DEVI void tma3d_mc(uint32_t dst, const CUtensorMap* tm, uint32_t bar, int c0, int c1, int c2) {
    asm volatile("cp.async.bulk.tensor.3d.shared::cluster.global.mbarrier::complete_tx::bytes.multicast::cluster [%0], [%1, {%3, %4, %5}], [%2], %6;"
                 :: "r"(dst), "l"(tm), "r"(bar), "r"(c0), "r"(c1), "r"(c2), "h"((uint16_t)3) : "memory");
}
DEVI void tma2d(uint32_t dst, const CUtensorMap* tm, uint32_t bar, int c0, int c1) {
    asm volatile("cp.async.bulk.tensor.2d.shared::cluster.global.mbarrier::complete_tx::bytes [%0], [%1, {%3, %4}], [%2];"
                 :: "r"(dst), "l"(tm), "r"(bar), "r"(c0), "r"(c1) : "memory");
}
DEVI void tma2d_prefetch(const CUtensorMap* tm, int c0, int c1) {
    asm volatile("cp.async.bulk.prefetch.tensor.2d.L2.global [%0, {%1, %2}];" :: "l"(tm), "r"(c0), "r"(c1) : "memory");
}
DEVI void tma2d_mc(uint32_t dst, const CUtensorMap* tm, uint32_t bar, int c0, int c1) {
    asm volatile("cp.async.bulk.tensor.2d.shared::cluster.global.mbarrier::complete_tx::bytes.multicast::cluster [%0], [%1, {%3, %4}], [%2], %5;"
                 :: "r"(dst), "l"(tm), "r"(bar), "r"(c0), "r"(c1), "h"((uint16_t)3) : "memory");
}
DEVI void mbar_arrive_both(uint32_t bar) {
    asm volatile("{\n.reg .b32 ra;\nmapa.shared::cluster.u32 ra, %0, 0;\nmbarrier.arrive.shared::cluster.b64 _, [ra];\n"
                 "mapa.shared::cluster.u32 ra, %0, 1;\nmbarrier.arrive.shared::cluster.b64 _, [ra];\n}" :: "r"(bar) : "memory");
}
DEVI void st_async_peer(uint32_t addr, uint32_t bar, uint32_t peer, uint32_t v) {
    asm volatile("{\n.reg .b32 ra, rb;\nmapa.shared::cluster.u32 ra, %0, %2;\nmapa.shared::cluster.u32 rb, %1, %2;\n"
                 "st.async.weak.shared::cluster.mbarrier::complete_tx::bytes.b32 [ra], %3, [rb];\n}" :: "r"(addr), "r"(bar), "r"(peer), "r"(v) : "memory");
}
DEVI void st_async_v2(uint32_t addr, uint32_t bar, uint32_t cta, float a, float b) {
    asm volatile("{\n.reg .b32 ra, rb;\nmapa.shared::cluster.u32 ra, %0, %2;\nmapa.shared::cluster.u32 rb, %1, %2;\n"
                 "st.async.weak.shared::cluster.mbarrier::complete_tx::bytes.v2.f32 [ra], {%3,%4}, [rb];\n}" :: "r"(addr), "r"(bar), "r"(cta), "f"(a), "f"(b) : "memory");
}
DEVI void st_async_v4(uint32_t addr, uint32_t bar, uint32_t cta, float a, float b, float c, float d) {
    asm volatile("{\n.reg .b32 ra, rb;\nmapa.shared::cluster.u32 ra, %0, %2;\nmapa.shared::cluster.u32 rb, %1, %2;\n"
                 "st.async.weak.shared::cluster.mbarrier::complete_tx::bytes.v4.f32 [ra], {%3,%4,%5,%6}, [rb];\n}" :: "r"(addr), "r"(bar), "r"(cta), "f"(a), "f"(b), "f"(c), "f"(d) : "memory");
}
DEVI void bulk_load(uint32_t dst, const void* src, uint32_t bytes, uint32_t bar) {
    asm volatile("cp.async.bulk.shared::cluster.global.mbarrier::complete_tx::bytes [%0], [%1], %2, [%3];" :: "r"(dst), "l"(src), "r"(bytes), "r"(bar) : "memory");
}
DEVI void cluster_arrive() { asm volatile("barrier.cluster.arrive.relaxed.aligned;" ::: "memory"); }
DEVI void cluster_wait() { asm volatile("barrier.cluster.wait.aligned;" ::: "memory"); }
DEVI void wg_fence() { asm volatile("wgmma.fence.sync.aligned;" ::: "memory"); }
DEVI void wg_commit() { asm volatile("wgmma.commit_group.sync.aligned;" ::: "memory"); }
template <int N> DEVI void wg_wait() { asm volatile("wgmma.wait_group.sync.aligned %0;" :: "n"(N) : "memory"); }
template <int ID, int N> DEVI void bar_sync() { asm volatile("bar.sync %0, %1;" :: "n"(ID), "n"(N) : "memory"); }
DEVI void spin_guard(unsigned& n) { if (++n > SPIN_MAX) __trap(); }
DEVI uint4 ld_relaxed_v4(const void* p) {
    uint4 v;
    asm volatile("ld.relaxed.gpu.global.v4.u32 {%0,%1,%2,%3}, [%4];" : "=r"(v.x), "=r"(v.y), "=r"(v.z), "=r"(v.w) : "l"(p) : "memory");
    return v;
}
DEVI void st_relaxed_v4(void* p, const uint4& v) {
    asm volatile("st.relaxed.gpu.global.v4.u32 [%0], {%1,%2,%3,%4};" :: "l"(p), "r"(v.x), "r"(v.y), "r"(v.z), "r"(v.w) : "memory");
}
DEVI unsigned ld_relaxed_u32(const void* p) { unsigned v; asm volatile("ld.relaxed.gpu.global.u32 %0, [%1];" : "=r"(v) : "l"(p) : "memory"); return v; }
DEVI unsigned ld_acquire_u32(const void* p) { unsigned v; asm volatile("ld.acquire.gpu.global.u32 %0, [%1];" : "=r"(v) : "l"(p) : "memory"); return v; }
DEVI void st_relaxed_u32(void* p, unsigned v) { asm volatile("st.relaxed.gpu.global.u32 [%0], %1;" :: "l"(p), "r"(v) : "memory"); }
DEVI void st_relaxed_v2(void* p, unsigned a, unsigned b) { asm volatile("st.relaxed.gpu.global.v2.u32 [%0], {%1,%2};" :: "l"(p), "r"(a), "r"(b) : "memory"); }
DEVI uint4 ld_gen_v4(const void* p) {
    uint4 v;
    asm volatile("ld.relaxed.gpu.v4.u32 {%0,%1,%2,%3}, [%4];" : "=r"(v.x), "=r"(v.y), "=r"(v.z), "=r"(v.w) : "l"(p) : "memory");
    return v;
}
DEVI void st_gen_v4(void* p, const uint4& v) { asm volatile("st.relaxed.gpu.v4.u32 [%0], {%1,%2,%3,%4};" :: "l"(p), "r"(v.x), "r"(v.y), "r"(v.z), "r"(v.w) : "memory"); }
DEVI float sqrt_approx(float x) { float y; asm("sqrt.approx.ftz.f32 %0, %1;" : "=f"(y) : "f"(x)); return y; }
DEVI void red_add_u32(unsigned* p, unsigned v) { asm volatile("red.relaxed.gpu.global.add.u32 [%0], %1;" :: "l"(p), "r"(v) : "memory"); }
DEVI void red_add_v4(void* p, float a, float b, float c, float d) {
    asm volatile("red.relaxed.gpu.global.add.v4.f32 [%0], {%1,%2,%3,%4};" :: "l"(p), "f"(a), "f"(b), "f"(c), "f"(d) : "memory");
}
DEVI float4 ld_relaxed_f4(const void* p) {
    float4 v;
    asm volatile("ld.relaxed.gpu.global.v4.f32 {%0,%1,%2,%3}, [%4];" : "=f"(v.x), "=f"(v.y), "=f"(v.z), "=f"(v.w) : "l"(p) : "memory");
    return v;
}
DEVI void tma3d_store(const CUtensorMap* tm, uint32_t src, int c0, int c1, int c2) {
    asm volatile("cp.async.bulk.tensor.3d.global.shared::cta.bulk_group [%0, {%2, %3, %4}], [%1];\ncp.async.bulk.commit_group;\ncp.async.bulk.wait_group.read 0;"
                 :: "l"(tm), "r"(src), "r"(c0), "r"(c1), "r"(c2) : "memory");
}
DEVI uint32_t lds_u16(uint32_t a) { unsigned short v; asm volatile("ld.shared.u16 %0, [%1];" : "=h"(v) : "r"(a)); return v; }
DEVI void fence_gpu() { asm volatile("fence.acq_rel.gpu;" ::: "memory"); }
DEVI uint4 ldg_v4(const void* p) {
    uint4 v;
    asm volatile("ld.global.L1::no_allocate.v4.u32 {%0,%1,%2,%3}, [%4];" : "=r"(v.x), "=r"(v.y), "=r"(v.z), "=r"(v.w) : "l"(p) : "memory");
    return v;
}
DEVI uint4 lds_v4(uint32_t a) { uint4 v; asm volatile("ld.shared.v4.u32 {%0,%1,%2,%3}, [%4];" : "=r"(v.x), "=r"(v.y), "=r"(v.z), "=r"(v.w) : "r"(a)); return v; }
DEVI void sts_v4(uint32_t a, const uint4& v) { asm volatile("st.shared.v4.u32 [%0], {%1,%2,%3,%4};" :: "r"(a), "r"(v.x), "r"(v.y), "r"(v.z), "r"(v.w) : "memory"); }
DEVI void sts_f4(uint32_t a, float x, float y, float z, float w) { asm volatile("st.shared.v4.f32 [%0], {%1,%2,%3,%4};" :: "r"(a), "f"(x), "f"(y), "f"(z), "f"(w) : "memory"); }
DEVI float2 lds_f2(uint32_t a) { float2 v; asm volatile("ld.shared.v2.f32 {%0,%1}, [%2];" : "=f"(v.x), "=f"(v.y) : "r"(a)); return v; }
DEVI float4 lds_f4(uint32_t a) { float4 v; asm volatile("ld.shared.v4.f32 {%0,%1,%2,%3}, [%4];" : "=f"(v.x), "=f"(v.y), "=f"(v.z), "=f"(v.w) : "r"(a)); return v; }
DEVI void ldsm4(uint32_t addr, uint32_t& a, uint32_t& b, uint32_t& c, uint32_t& d) {
    asm volatile("ldmatrix.sync.aligned.m8n8.x4.shared.b16 {%0,%1,%2,%3}, [%4];" : "=r"(a), "=r"(b), "=r"(c), "=r"(d) : "r"(addr));
}
DEVI void ldsm4_if(bool on, uint32_t addr, uint32_t (&v)[4]) {
    asm volatile("{\n.reg .pred p;\nsetp.ne.b32 p, %5, 0;\n@p ldmatrix.sync.aligned.m8n8.x4.shared.b16 {%0,%1,%2,%3}, [%4];\n}"
                 : "+r"(v[0]), "+r"(v[1]), "+r"(v[2]), "+r"(v[3]) : "r"(addr), "r"((uint32_t)on));
}
DEVI void ldsm4t(uint32_t addr, uint32_t (&v)[4]) {
    asm volatile("ldmatrix.sync.aligned.m8n8.x4.trans.shared.b16 {%0,%1,%2,%3}, [%4];" : "=r"(v[0]), "=r"(v[1]), "=r"(v[2]), "=r"(v[3]) : "r"(addr));
}
DEVI void ldsm2(uint32_t addr, uint32_t& a, uint32_t& b) { asm volatile("ldmatrix.sync.aligned.m8n8.x2.shared.b16 {%0,%1}, [%2];" : "=r"(a), "=r"(b) : "r"(addr)); }
DEVI void cp_async16(uint32_t dst, const void* src) { asm volatile("cp.async.cg.shared.global [%0], [%1], 16;" :: "r"(dst), "l"(src) : "memory"); }
DEVI void prefetch_l2_bulk(const void* p, uint32_t bytes) { asm volatile("cp.async.bulk.prefetch.L2.global [%0], %1;" :: "l"(p), "r"(bytes) : "memory"); }
DEVI void sts_u16(uint32_t a, uint32_t v) { asm volatile("st.shared.u16 [%0], %1;" :: "r"(a), "h"((unsigned short)v) : "memory"); }
DEVI uint32_t hfma2(uint32_t a, uint32_t b, uint32_t c) { uint32_t d; asm("fma.rn.bf16x2 %0, %1, %2, %3;" : "=r"(d) : "r"(a), "r"(b), "r"(c)); return d; }
DEVI uint32_t imul(uint32_t a, uint32_t b) { uint32_t d; asm("mul.lo.u32 %0, %1, %2;" : "=r"(d) : "r"(a), "r"(b)); return d; }
DEVI float tanh_f(float x) { float t; asm("tanh.approx.f32 %0, %1;" : "=f"(t) : "f"(x)); return t; }
DEVI void stsm4(uint32_t addr, uint32_t a, uint32_t b, uint32_t c, uint32_t d) {
    asm volatile("stmatrix.sync.aligned.m8n8.x4.shared.b16 [%0], {%1,%2,%3,%4};" :: "r"(addr), "r"(a), "r"(b), "r"(c), "r"(d) : "memory");
}
DEVI uint32_t movm(uint32_t a) { uint32_t d; asm("movmatrix.sync.aligned.m8n8.trans.b16 %0, %1;" : "=r"(d) : "r"(a)); return d; }
DEVI void mma16(float (&c)[4], uint32_t a0, uint32_t a1, uint32_t a2, uint32_t a3, uint32_t b0, uint32_t b1) {
    asm("mma.sync.aligned.m16n8k16.row.col.f32.bf16.bf16.f32 {%0,%1,%2,%3}, {%4,%5,%6,%7}, {%8,%9}, {%0,%1,%2,%3};"
                 : "+f"(c[0]), "+f"(c[1]), "+f"(c[2]), "+f"(c[3]) : "r"(a0), "r"(a1), "r"(a2), "r"(a3), "r"(b0), "r"(b1));
}
DEVI void mma8(float (&c)[4], uint32_t a0, uint32_t a1, uint32_t b0) {
    asm("mma.sync.aligned.m16n8k8.row.col.f32.bf16.bf16.f32 {%0,%1,%2,%3}, {%4,%5}, {%6}, {%0,%1,%2,%3};"
                 : "+f"(c[0]), "+f"(c[1]), "+f"(c[2]), "+f"(c[3]) : "r"(a0), "r"(a1), "r"(b0));
}
DEVI uint32_t pack_bf16(float lo, float hi) { uint32_t d; asm("cvt.rn.bf16x2.f32 %0, %1, %2;" : "=r"(d) : "f"(hi), "f"(lo)); return d; }
DEVI float bf_lo(uint32_t v) { return __uint_as_float(v << 16); }
DEVI float bf_hi(uint32_t v) { return __uint_as_float(v & 0xffff0000u); }
DEVI float bfr(float x) { return __bfloat162float(__float2bfloat16_rn(x)); }
DEVI uint32_t tagf(float v, unsigned tag) { return (__float_as_uint(v) & ~15u) | (tag & 15); }
DEVI float ex2(float x) { float y; asm("ex2.approx.ftz.f32 %0, %1;" : "=f"(y) : "f"(x)); return y; }
DEVI float rcp(float x) { float y; asm("rcp.approx.ftz.f32 %0, %1;" : "=f"(y) : "f"(x)); return y; }
DEVI float sigmoid_f(float x) { return rcp(1.0f + ex2(x * -1.4426950408889634f)); }
DEVI float silu_f(float x) { const float h = 0.5f * x; float t; asm("tanh.approx.f32 %0, %1;" : "=f"(t) : "f"(h)); return fmaf(h, t, h); }
DEVI uint32_t hsub2(uint32_t a, uint32_t b) { uint32_t d; asm("sub.rn.bf16x2 %0, %1, %2;" : "=r"(d) : "r"(a), "r"(b)); return d; }
DEVI uint32_t hadd2(uint32_t a, uint32_t b) { uint32_t d; asm("add.rn.bf16x2 %0, %1, %2;" : "=r"(d) : "r"(a), "r"(b)); return d; }
DEVI uint32_t hmul2(uint32_t a, uint32_t b) { uint32_t d; asm("mul.rn.bf16x2 %0, %1, %2;" : "=r"(d) : "r"(a), "r"(b)); return d; }
DEVI uint32_t dup_hi(float x) { return __byte_perm(__float_as_uint(x), 0, 0x3232); }
DEVI void sts_u32(uint32_t a, uint32_t v) { asm volatile("st.shared.u32 [%0], %1;" :: "r"(a), "r"(v) : "memory"); }
DEVI void sts_f2(uint32_t a, float x, float y) { asm volatile("st.shared.v2.f32 [%0], {%1,%2};" :: "r"(a), "f"(x), "f"(y) : "memory"); }
DEVI uint2 lds_v2(uint32_t a) { uint2 v; asm volatile("ld.shared.v2.u32 {%0,%1}, [%2];" : "=r"(v.x), "=r"(v.y) : "r"(a)); return v; }
DEVI uint32_t lds_u32(uint32_t a) { uint32_t v; asm volatile("ld.shared.u32 %0, [%1];" : "=r"(v) : "r"(a)); return v; }
DEVI float lds_f32(uint32_t a) { float v; asm volatile("ld.shared.f32 %0, [%1];" : "=f"(v) : "r"(a)); return v; }
DEVI float shfl_x(float v, int o) { return __shfl_xor_sync(0xffffffffu, v, o); }

DEVI void wgmma_rs_n192(float (&d)[120], uint32_t a0, uint32_t a1, uint32_t a2, uint32_t a3, uint32_t blo, uint32_t scale_d) {
    asm volatile("{\n.reg .b64 db;\n.reg .pred p;\n"
        "setp.ne.b32 p, %101, 0;\n"
        "mov.b64 db, {%100, 0x40000040};\n"
        "wgmma.mma_async.sync.aligned.m64n192k16.f32.bf16.bf16 "
        "{%0, %1, %2, %3, %4, %5, %6, %7, %8, %9, %10, %11, %12, %13, %14, %15, %16, %17, %18, %19, %20, %21, %22, %23, %24, %25, %26, %27, %28, %29, %30, %31, %32, %33, %34, %35, %36, %37, %38, %39, %40, %41, %42, %43, %44, %45, %46, %47, %48, %49, %50, %51, %52, %53, %54, %55, %56, %57, %58, %59, %60, %61, %62, %63, %64, %65, %66, %67, %68, %69, %70, %71, %72, %73, %74, %75, %76, %77, %78, %79, %80, %81, %82, %83, %84, %85, %86, %87, %88, %89, %90, %91, %92, %93, %94, %95}, "
        "{%96, %97, %98, %99}, db, p, 1, 1, 1;\n}\n"
        : "+f"(d[0]), "+f"(d[1]), "+f"(d[2]), "+f"(d[3]), "+f"(d[4]), "+f"(d[5]), "+f"(d[6]), "+f"(d[7]), "+f"(d[8]), "+f"(d[9]), "+f"(d[10]), "+f"(d[11]), "+f"(d[12]), "+f"(d[13]), "+f"(d[14]), "+f"(d[15]), "+f"(d[16]), "+f"(d[17]), "+f"(d[18]), "+f"(d[19]), "+f"(d[20]), "+f"(d[21]), "+f"(d[22]), "+f"(d[23]), "+f"(d[24]), "+f"(d[25]), "+f"(d[26]), "+f"(d[27]), "+f"(d[28]), "+f"(d[29]), "+f"(d[30]), "+f"(d[31]), "+f"(d[32]), "+f"(d[33]), "+f"(d[34]), "+f"(d[35]), "+f"(d[36]), "+f"(d[37]), "+f"(d[38]), "+f"(d[39]), "+f"(d[40]), "+f"(d[41]), "+f"(d[42]), "+f"(d[43]), "+f"(d[44]), "+f"(d[45]), "+f"(d[46]), "+f"(d[47]), "+f"(d[48]), "+f"(d[49]), "+f"(d[50]), "+f"(d[51]), "+f"(d[52]), "+f"(d[53]), "+f"(d[54]), "+f"(d[55]), "+f"(d[56]), "+f"(d[57]), "+f"(d[58]), "+f"(d[59]), "+f"(d[60]), "+f"(d[61]), "+f"(d[62]), "+f"(d[63]), "+f"(d[64]), "+f"(d[65]), "+f"(d[66]), "+f"(d[67]), "+f"(d[68]), "+f"(d[69]), "+f"(d[70]), "+f"(d[71]), "+f"(d[72]), "+f"(d[73]), "+f"(d[74]), "+f"(d[75]), "+f"(d[76]), "+f"(d[77]), "+f"(d[78]), "+f"(d[79]), "+f"(d[80]), "+f"(d[81]), "+f"(d[82]), "+f"(d[83]), "+f"(d[84]), "+f"(d[85]), "+f"(d[86]), "+f"(d[87]), "+f"(d[88]), "+f"(d[89]), "+f"(d[90]), "+f"(d[91]), "+f"(d[92]), "+f"(d[93]), "+f"(d[94]), "+f"(d[95])
        : "r"(a0), "r"(a1), "r"(a2), "r"(a3), "r"(blo), "r"(scale_d));
}
DEVI void wgmma_rs_n48(float (&d)[120], uint32_t a0, uint32_t a1, uint32_t a2, uint32_t a3, uint32_t blo, uint32_t scale_d) {
    asm volatile("{\n.reg .b64 db;\n.reg .pred p;\n"
        "setp.ne.b32 p, %29, 0;\n"
        "mov.b64 db, {%28, 0xc0000010};\n"
        "wgmma.mma_async.sync.aligned.m64n48k16.f32.bf16.bf16 "
        "{%0, %1, %2, %3, %4, %5, %6, %7, %8, %9, %10, %11, %12, %13, %14, %15, %16, %17, %18, %19, %20, %21, %22, %23}, "
        "{%24, %25, %26, %27}, db, p, 1, 1, 1;\n}\n"
        : "+f"(d[96]), "+f"(d[97]), "+f"(d[98]), "+f"(d[99]), "+f"(d[100]), "+f"(d[101]), "+f"(d[102]), "+f"(d[103]), "+f"(d[104]), "+f"(d[105]), "+f"(d[106]), "+f"(d[107]), "+f"(d[108]), "+f"(d[109]), "+f"(d[110]), "+f"(d[111]), "+f"(d[112]), "+f"(d[113]), "+f"(d[114]), "+f"(d[115]), "+f"(d[116]), "+f"(d[117]), "+f"(d[118]), "+f"(d[119])
        : "r"(a0), "r"(a1), "r"(a2), "r"(a3), "r"(blo), "r"(scale_d));
}
DEVI void wgmma_rs_n192x(float (&d)[120], uint32_t a0, uint32_t a1, uint32_t a2, uint32_t a3, uint32_t blo) {
    asm volatile("{\n.reg .b64 db;\n.reg .pred p;\n"
        "mov.b64 db, {%100, 0x40000000};\n"
        "wgmma.mma_async.sync.aligned.m64n192k16.f32.bf16.bf16 "
        "{%0, %1, %2, %3, %4, %5, %6, %7, %8, %9, %10, %11, %12, %13, %14, %15, %16, %17, %18, %19, %20, %21, %22, %23, %24, %25, %26, %27, %28, %29, %30, %31, %32, %33, %34, %35, %36, %37, %38, %39, %40, %41, %42, %43, %44, %45, %46, %47, %48, %49, %50, %51, %52, %53, %54, %55, %56, %57, %58, %59, %60, %61, %62, %63, %64, %65, %66, %67, %68, %69, %70, %71, %72, %73, %74, %75, %76, %77, %78, %79, %80, %81, %82, %83, %84, %85, %86, %87, %88, %89, %90, %91, %92, %93, %94, %95}, "
        "{%96, %97, %98, %99}, db, 1, 1, 1, 1;\n}\n"
        : "+f"(d[0]), "+f"(d[1]), "+f"(d[2]), "+f"(d[3]), "+f"(d[4]), "+f"(d[5]), "+f"(d[6]), "+f"(d[7]), "+f"(d[8]), "+f"(d[9]), "+f"(d[10]), "+f"(d[11]), "+f"(d[12]), "+f"(d[13]), "+f"(d[14]), "+f"(d[15]), "+f"(d[16]), "+f"(d[17]), "+f"(d[18]), "+f"(d[19]), "+f"(d[20]), "+f"(d[21]), "+f"(d[22]), "+f"(d[23]), "+f"(d[24]), "+f"(d[25]), "+f"(d[26]), "+f"(d[27]), "+f"(d[28]), "+f"(d[29]), "+f"(d[30]), "+f"(d[31]), "+f"(d[32]), "+f"(d[33]), "+f"(d[34]), "+f"(d[35]), "+f"(d[36]), "+f"(d[37]), "+f"(d[38]), "+f"(d[39]), "+f"(d[40]), "+f"(d[41]), "+f"(d[42]), "+f"(d[43]), "+f"(d[44]), "+f"(d[45]), "+f"(d[46]), "+f"(d[47]), "+f"(d[48]), "+f"(d[49]), "+f"(d[50]), "+f"(d[51]), "+f"(d[52]), "+f"(d[53]), "+f"(d[54]), "+f"(d[55]), "+f"(d[56]), "+f"(d[57]), "+f"(d[58]), "+f"(d[59]), "+f"(d[60]), "+f"(d[61]), "+f"(d[62]), "+f"(d[63]), "+f"(d[64]), "+f"(d[65]), "+f"(d[66]), "+f"(d[67]), "+f"(d[68]), "+f"(d[69]), "+f"(d[70]), "+f"(d[71]), "+f"(d[72]), "+f"(d[73]), "+f"(d[74]), "+f"(d[75]), "+f"(d[76]), "+f"(d[77]), "+f"(d[78]), "+f"(d[79]), "+f"(d[80]), "+f"(d[81]), "+f"(d[82]), "+f"(d[83]), "+f"(d[84]), "+f"(d[85]), "+f"(d[86]), "+f"(d[87]), "+f"(d[88]), "+f"(d[89]), "+f"(d[90]), "+f"(d[91]), "+f"(d[92]), "+f"(d[93]), "+f"(d[94]), "+f"(d[95])
        : "r"(a0), "r"(a1), "r"(a2), "r"(a3), "r"(blo));
}
DEVI void wgmma_rs_n48x(float (&d)[120], uint32_t a0, uint32_t a1, uint32_t a2, uint32_t a3, uint32_t blo) {
    asm volatile("{\n.reg .b64 db;\n.reg .pred p;\n"
        "mov.b64 db, {%28, 0xc0000000};\n"
        "wgmma.mma_async.sync.aligned.m64n48k16.f32.bf16.bf16 "
        "{%0, %1, %2, %3, %4, %5, %6, %7, %8, %9, %10, %11, %12, %13, %14, %15, %16, %17, %18, %19, %20, %21, %22, %23}, "
        "{%24, %25, %26, %27}, db, 1, 1, 1, 1;\n}\n"
        : "+f"(d[96]), "+f"(d[97]), "+f"(d[98]), "+f"(d[99]), "+f"(d[100]), "+f"(d[101]), "+f"(d[102]), "+f"(d[103]), "+f"(d[104]), "+f"(d[105]), "+f"(d[106]), "+f"(d[107]), "+f"(d[108]), "+f"(d[109]), "+f"(d[110]), "+f"(d[111]), "+f"(d[112]), "+f"(d[113]), "+f"(d[114]), "+f"(d[115]), "+f"(d[116]), "+f"(d[117]), "+f"(d[118]), "+f"(d[119])
        : "r"(a0), "r"(a1), "r"(a2), "r"(a3), "r"(blo));
}
DEVI void wgmma_rs_n80(float (&d)[40], uint32_t a0, uint32_t a1, uint32_t a2, uint32_t a3, uint32_t blo, uint32_t scale_d) {
    asm volatile("{\n.reg .b64 db;\n.reg .pred p;\n"
        "setp.ne.b32 p, %45, 0;\n"
        "mov.b64 db, {%44, 0x40000040};\n"
        "wgmma.mma_async.sync.aligned.m64n80k16.f32.bf16.bf16 "
        "{%0, %1, %2, %3, %4, %5, %6, %7, %8, %9, %10, %11, %12, %13, %14, %15, %16, %17, %18, %19, %20, %21, %22, %23, %24, %25, %26, %27, %28, %29, %30, %31, %32, %33, %34, %35, %36, %37, %38, %39}, "
        "{%40, %41, %42, %43}, db, p, 1, 1, 1;\n}\n"
        : "+f"(d[0]), "+f"(d[1]), "+f"(d[2]), "+f"(d[3]), "+f"(d[4]), "+f"(d[5]), "+f"(d[6]), "+f"(d[7]), "+f"(d[8]), "+f"(d[9]), "+f"(d[10]), "+f"(d[11]), "+f"(d[12]), "+f"(d[13]), "+f"(d[14]), "+f"(d[15]), "+f"(d[16]), "+f"(d[17]), "+f"(d[18]), "+f"(d[19]), "+f"(d[20]), "+f"(d[21]), "+f"(d[22]), "+f"(d[23]), "+f"(d[24]), "+f"(d[25]), "+f"(d[26]), "+f"(d[27]), "+f"(d[28]), "+f"(d[29]), "+f"(d[30]), "+f"(d[31]), "+f"(d[32]), "+f"(d[33]), "+f"(d[34]), "+f"(d[35]), "+f"(d[36]), "+f"(d[37]), "+f"(d[38]), "+f"(d[39])
        : "r"(a0), "r"(a1), "r"(a2), "r"(a3), "r"(blo), "r"(scale_d));
}
DEVI void wgmma_ss_n80(float (&d)[40], uint32_t alo, uint32_t blo) {
    asm volatile("{\n.reg .b64 da, db;\n"
        "mov.b64 da, {%40, 0x10};\n"
        "mov.b64 db, {%41, 0x40000040};\n"
        "wgmma.mma_async.sync.aligned.m64n80k16.f32.bf16.bf16 "
        "{%0, %1, %2, %3, %4, %5, %6, %7, %8, %9, %10, %11, %12, %13, %14, %15, %16, %17, %18, %19, %20, %21, %22, %23, %24, %25, %26, %27, %28, %29, %30, %31, %32, %33, %34, %35, %36, %37, %38, %39}, "
        "da, db, 1, 1, 1, 0, 1;\n}\n"
        : "+f"(d[0]), "+f"(d[1]), "+f"(d[2]), "+f"(d[3]), "+f"(d[4]), "+f"(d[5]), "+f"(d[6]), "+f"(d[7]), "+f"(d[8]), "+f"(d[9]), "+f"(d[10]), "+f"(d[11]), "+f"(d[12]), "+f"(d[13]), "+f"(d[14]), "+f"(d[15]), "+f"(d[16]), "+f"(d[17]), "+f"(d[18]), "+f"(d[19]), "+f"(d[20]), "+f"(d[21]), "+f"(d[22]), "+f"(d[23]), "+f"(d[24]), "+f"(d[25]), "+f"(d[26]), "+f"(d[27]), "+f"(d[28]), "+f"(d[29]), "+f"(d[30]), "+f"(d[31]), "+f"(d[32]), "+f"(d[33]), "+f"(d[34]), "+f"(d[35]), "+f"(d[36]), "+f"(d[37]), "+f"(d[38]), "+f"(d[39])
        : "r"(alo), "r"(blo));
}

DEVI unsigned redux_max(unsigned v) { return __reduce_max_sync(0xffffffffu, v); }

DEVI void service_cta(Scratch* __restrict__ sc, const __nv_bfloat16* __restrict__ x, const __nv_bfloat16* __restrict__ wr, uint32_t sb, int h, int tid) {
    const int warp = tid >> 5, lane = tid & 31;
    Outbox* const box = &sc->box[h];
    const unsigned tag = ld_relaxed_u32(&sc->epoch[(NCTA + h) * 32]) + 1;
    if (tid < 256) st_relaxed_v4(&box->msg[0] + tid, make_uint4(EMPTY_WORD, EMPTY_WORD, EMPTY_WORD, EMPTY_WORD));
    __syncthreads();
    unsigned spins = 0;
    if (warp == 0) {
        fence_gpu();
        if (lane < 2) st_relaxed_v4(&sc->open[h][lane * 4], make_uint4(tag, tag, tag, tag));
    }
    if (warp >= 8) {
        const int t = tid - 256;
        float wsum = 0.f;
        __nanosleep(1000);
#pragma unroll
        for (int j = 0; j < 10; j++) { const uint32_t v = reinterpret_cast<const uint32_t*>(wr)[lane + 32 * j]; wsum += bf_lo(v) + bf_hi(v); }
#pragma unroll
        for (int o = 1; o < 32; o <<= 1) wsum += shfl_x(wsum, o);
        uint4 q[4];
        const uint4* src = reinterpret_cast<const uint4*>(&sc->rowinfo[0][0][0]) + t;
#pragma unroll
        for (int j = 0; j < 4; j++) q[j].y = q[j].w = tag - 1;
        while (true) {
            unsigned bad = 0;
#pragma unroll
            for (int j = 0; j < 4; j++) if (((q[j].y ^ tag) | (q[j].w ^ tag)) & 15) q[j] = ld_relaxed_v4(src + 256 * j);
            __syncwarp();
#pragma unroll
            for (int j = 0; j < 4; j++) bad |= (q[j].y ^ tag) | (q[j].w ^ tag);
            if (__all_sync(0xffffffffu, (bad & 15) == 0)) break;
            if (spins == 0) while (!__any_sync(0xffffffffu, ((ld_relaxed_v4(src).y ^ tag) & 15) == 0)) { __nanosleep(100); spin_guard(spins); }
            spin_guard(spins);
        }
        if (t == 0) TL(2);
        unsigned a = 0, b = 0;
#pragma unroll
        for (int j = 0; j < 8; j++) {
            const uint32_t info = (j & 1) ? q[j >> 1].z : q[j >> 1].x;
            const uint32_t u = pack_bf16(fmaf(-bf_lo(info), wsum, __uint_as_float((j & 1) ? q[j >> 1].w : q[j >> 1].y)) * rcp(bf_hi(info)), 0.f);
            const int row = ((j >> 1) * 4 + (t >> 6)) * 128 + 4 * (t & 31) + 2 * (j & 1) + ((t >> 5) & 1);
            const unsigned key = (((u & 0x8000u) ? (u ^ 0xffffu) : (u | 0x8000u)) << 16) | ((2047 - row) << 5);
            b = max(b, min(a, key)); a = max(a, key);
        }
        unsigned k1 = redux_max(a), k2 = redux_max(a == k1 ? b : a);
        if (lane == 0) sts_f2(sb + 8192 + (warp - 8) * 8, __uint_as_float(k1), __uint_as_float(k2));
        bar_sync<2, 256>();
        a = lds_u32(sb + 8192 + (lane & 15) * 4);
        k1 = redux_max(a); k2 = redux_max(a == k1 ? 0u : a);
        if (t < 160) {
            const int tk = t >= 80, sel = 2047 - (((tk ? k2 : k1) >> 5) & 2047);
            const uint4 xq = ldg_v4(reinterpret_cast<const uint4*>(x + sel * DM) + t - tk * 80);
            const unsigned info = ld_relaxed_u32(&sc->rowinfo[sel >> 7][sel & 1][(sel & 127) >> 1]);
            const uint32_t mm = __byte_perm(info, 0, 0x1010);
            const float rs = rcp(bf_hi(info));
            uint32_t o[4];
#pragma unroll
            for (int e = 0; e < 4; e++) { const uint32_t d = hsub2((&xq.x)[e], mm); o[e] = pack_bf16(bf_lo(d) * rs, bf_hi(d) * rs); }
            st_relaxed_v4(&box->msg[t + tk], make_uint4(o[0], o[1], o[2], o[3]));
            sts_v4(sb + SM_XSEL + (t + tk) * 16, make_uint4(o[0], o[1], o[2], o[3]));
        } else if (t == 160) {
            const uint4 top = make_uint4(2047 - ((k1 >> 5) & 2047), 2047 - ((k2 >> 5) & 2047), k1, k2);
            st_relaxed_v4(&box->msg[80], top); sts_v4(sb + SM_TOP, top);
        }
        if (t == 0) TL(3);
    }
    __syncthreads();
    const uint4* src = &sc->yp[2 * h + (warp >> 3)][warp & 7][0];
    uint4 v[7]; unsigned u[7];
#pragma unroll
    for (int j = 0; j < 7; j++) v[j].x = u[j] = (j == 6 && (warp & 7) >= 6) ? tag : tag - 1;
    spins = 0;
    while (NMOE) {
        unsigned bad = 0;
#pragma unroll
        for (int j = 0; j < 7; j++)
            if (((v[j].x ^ tag) | (u[j] ^ tag)) & 15) { v[j] = ld_relaxed_v4(src + j * 320 + lane); u[j] = ld_relaxed_u32(reinterpret_cast<const unsigned*>(src + j * 320 + 32) + lane); }
        __syncwarp();
#pragma unroll
        for (int j = 0; j < 7; j++) bad |= (v[j].x ^ tag) | (u[j] ^ tag);
        if (__all_sync(0xffffffffu, (bad & 15) == 0)) break;
        if (spins == 0) while (!__any_sync(0xffffffffu, ((ld_relaxed_u32(src + min(lane & 7, 5) * 320 + 32) ^ tag) & 15) == 0)) { __nanosleep(100); spin_guard(spins); }
        spin_guard(spins);
    }
    if (tid == 0) TL(4);
    float y[5] = {0.f, 0.f, 0.f, 0.f, 0.f};
#pragma unroll
    for (int j = 0; j < 7; j++) {
        if (NMOE && (j < 6 || (warp & 7) < 6)) {
            y[0] += __uint_as_float(v[j].x); y[1] += __uint_as_float(v[j].y); y[2] += __uint_as_float(v[j].z); y[3] += __uint_as_float(v[j].w); y[4] += __uint_as_float(u[j]);
        }
    }
#pragma unroll
    for (int e = 0; e < 5; e++) sts_u32(sb + (warp * 160 + e * 32 + lane) * 4, __float_as_uint(y[e]));
    __syncthreads();
    if (warp < 10) {
        const int gi = warp >= 5, e = warp - 5 * gi, tk = lane & 1, col = e * 16 + (lane >> 2) + 4 * (lane & 2);
        float sum = 0.f;
#pragma unroll
        for (int j = 0; j < 8; j++) sum += lds_f32(sb + ((gi * 8 + j) * 160 + e * 32 + lane) * 4);
        const uint32_t ks = lds_u32(sb + SM_TOP + 8 + tk * 4) >> 16;
        const float sg = bfr(sigmoid_f(__uint_as_float(((ks & 0x8000u) ? (ks & 0x7fffu) : (ks ^ 0xffffu)) << 16)));
        sts_u16(sb + 16384 + gi * 512 + tk * 160 + col * 2,
                pack_bf16(silu_f(bfr(bf_lo(lds_u16(sb + SM_XSEL + tk * 1296 + ((2 * h + gi) * 80 + col) * 2)) + bfr(bfr(sum) * sg))), 0.f));
        bar_sync<1, 320>();
        if (warp < 2 && lane < 20) st_relaxed_v4(&box->gt[warp][lane], lds_v4(sb + 16384 + tid * 16));
    }
    if (tid == 0) { st_relaxed_u32(&sc->epoch[(NCTA + h) * 32], tag); TL(5); }
}

template <int ODD, int HALF> DEVI void pack_kv(const float (&acc)[120], uint32_t (&K)[10][2], uint32_t (&V)[10][2]) {
#pragma unroll
    for (int b = 0; b < 10; b++) {
        const int pb = ODD ? (b + 8) % 10 : b, jk = pb < 8 ? 8 + pb : 18 + pb, jv = pb < 8 ? 16 + pb : 20 + pb;
        V[b][HALF] = movm(pack_bf16(acc[4 * jv + 2 * HALF], acc[4 * jv + 2 * HALF + 1]));
        K[b][HALF] = pack_bf16(acc[4 * jk + 2 * HALF], acc[4 * jk + 2 * HALF + 1]);
    }
}
template <int ODD> DEVI void pack_q(const float (&acc)[120], uint32_t (&Q)[10][2]) {
#pragma unroll
    for (int b = 0; b < 10; b++) {
        const int pb = ODD ? (b + 8) % 10 : b, jq = pb < 8 ? pb : 16 + pb;
        Q[b][0] = pack_bf16(acc[4 * jq], acc[4 * jq + 1]); Q[b][1] = pack_bf16(acc[4 * jq + 2], acc[4 * jq + 3]);
    }
}

#define KROT 5
#define WOP 8
#define SIDE_N -1
#define PIPE_POLL 0
#define NSIDE 4
#define WO_S 6
#define TAIL_NS 50
#define WO_GATE 2
#define MSG_NS 800
#define T2_NS 0
#define JL 6
#define G7T 10
#define PRE_NS 0
#define POLL2 0
#define POLL2_GAP 60
#define GI_T 0
#define SPLIT 3
#define RS_PACE(t) (t)
#define ATS(i)
#define SRC(i) ((i) == 0 ? g : ((i) - 1 < g ? (i) - 1 : (i)))

__global__ void __cluster_dims__(2, 1, 1) __launch_bounds__(NTHREADS, 1) fused_kernel(
    Scratch* __restrict__ sc,
    const __nv_bfloat16* __restrict__ x, const __nv_bfloat16* __restrict__ wqkv, const __nv_bfloat16* __restrict__ wo, const __nv_bfloat16* __restrict__ wr,
    const __nv_bfloat16* __restrict__ wd, __nv_bfloat16* __restrict__ out, const int by_sm, const __grid_constant__ Roles roles,
    const __grid_constant__ CUtensorMap tm_x, const __grid_constant__ CUtensorMap tm_w, const __grid_constant__ CUtensorMap tm_wt,
    const __grid_constant__ CUtensorMap tm_wo, const __grid_constant__ CUtensorMap tm_d,
    const __grid_constant__ CUtensorMap tm_g, const __grid_constant__ CUtensorMap tm_u, const __grid_constant__ CUtensorMap tm_o)
{
    extern __shared__ __align__(1024) unsigned char smem[];
    const uint32_t bid = blockIdx.x, tid = threadIdx.x;
    uint32_t sb, smid;
    asm volatile("mov.u32 %0, %1;" : "=r"(sb) : "r"(smem_u32(smem)));
    asm volatile("mov.u32 %0, %%smid;" : "=r"(smid));
    const unsigned cta = roles.pair[(by_sm ? smid : bid) >> 1] * 2 + (bid & 1);
    const int warp = __shfl_sync(0xffffffffu, tid >> 5, 0), lane = tid & 31;
    const uint32_t bars = sb + SM_BAR;
#define BAR_COUNT(s) ((s >> 2) == 1 ? 4 : (s >= BAR_AE ? (s >= BAR_FA ? 1 : (s == BAR_AE + 5 ? 2 : 4)) : (s >= BAR_PA ? 8 : (s == BAR_CS ? 4 : (s >= BAR_OE + 2 ? 2 : 1)))))
#define INIT_BARS(a, b) do { if (elect_one()) { _Pragma("unroll") for (int s = a; s < b; s++) if (s != BAR_FA || (a) == BAR_FA) mbar_init(bars + s * 8, BAR_COUNT(s)); \
        asm volatile("fence.mbarrier_init.release.cluster;" ::: "memory"); } __syncwarp(); } while (0)
    if (warp >= 8) {
        if (warp == 8) INIT_BARS(BAR_FA, BAR_FA + 1);
        else if (warp == 9) INIT_BARS(0, 23);
        else if (warp == 10) INIT_BARS(23, NBAR);
    }
    cluster_arrive();
    if (warp < 2) {
        const uint32_t i = tid - 32;
        if (tid < 30 && bid < NCTA) asm volatile("prefetch.global.L2 [%0];" :: "l"(reinterpret_cast<const char*>(wqkv) + (bid * 15 + tid + (tid >= 15 ? KROT * 1920 - 15 : 0)) * 128) : "memory");
        if (i < 16) asm volatile("prefetch.global.L2 [%0];" :: "l"(bid < NCTA ? reinterpret_cast<const char*>(x) + (bid * 16 + i) * 1280 + (bid & 16) * (KROT * 8)
                                                                             : reinterpret_cast<const char*>(wr) + min(i, 9u) * 128) : "memory");
    }
    if (cta >= NCTA) { cluster_wait(); service_cta(sc, x, wr, sb, cta - NCTA, tid); return; }
    const int rank = cta & 1, g = (cta >> 1) & 7, G = cta >> 4, m = 2 * G + rank, odd = g & 1;
    const int k0 = (G & 1) * KROT * 64;
    const int cm = g * 80 + odd * 16, ct = g * 80 + 64 - odd * 64;

#define NP0 2
#define TILE_X(kt, kk) tma3d(sb + (-(kt) & 3) * STAGE, &tm_x, bars + (BAR_FA + ((kt) & 3)) * 8, kk, m * 64, 0)
#define TILE_W(kt, kk) do { const uint32_t fb_ = bars + (BAR_FULL + ((kt) & 3)) * 8, st_ = sb + (-(kt) & 3) * STAGE + OFF_B; \
        tma3d_mc(st_ + rank * B_HALF, &tm_w, fb_, cm, (kk) + rank * 32, 0); \
        tma3d(st_ + 12288, &tm_wt, fb_, ct, kk, 0); tma3d(st_ + B_HALF + 12288, &tm_wt, fb_, ct, (kk) + 32, 0); } while (0)
    if (warp == 8) {
        if (elect_one()) { mbar_expect_tx(bars + BAR_FA * 8, OFF_B); TILE_X(0, k0); }
        cluster_wait();
        if (elect_one()) {
            mbar_expect_tx(bars + BAR_FULL * 8, 2 * B_HALF);
            TILE_W(0, k0);
            mbar_expect_tx(bars + BAR_WR * 8, 1280); bulk_load(sb + SM_XSEL, wr, 1280, bars + BAR_WR * 8);
            TL(16);
#pragma unroll
            for (int kt = 1; kt < NP0; kt++) {
                mbar_expect_tx(bars + (BAR_FA + kt) * 8, OFF_B); mbar_expect_tx(bars + (BAR_FULL + kt) * 8, 2 * B_HALF);
                TILE_X(kt, k0 + kt * 64); TILE_W(kt, k0 + kt * 64);
                if (kt == 1) TL(29);
            }
        }
        __syncwarp();
    }
    if (warp >= 8) {
        asm volatile("setmaxnreg.dec.sync.aligned.u32 64;");
        const int mi = g < 6 ? G * 6 + g : 46 + G;
        const bool moe = g < 6 || (g == 6 && G >= 2);
        if (warp == 8) {
            const CUtensorMap* tm_gu = rank ? &tm_u : &tm_g;
            if (elect_one()) { mbar_expect_tx(bars + BAR_WO * 8, 81920); mbar_expect_tx(bars + BAR_GW * 8, 40960); mbar_expect_tx(bars + BAR_DW * 8, 20480); }
#pragma unroll 1
            for (int kt = NP0; kt < 13; kt++) {
                if (kt >= 4) { if (kt < 4 + JL) mbar_wait(bars + (BAR_AE + kt - 4) * 8, 0); mbar_wait(bars + (BAR_EMPTY + (kt & 3)) * 8, ((kt >> 2) - 1) & 1); }
                if (elect_one()) {
                    if (kt < 10) {
                        const int kk = kt * 64 + (kt < 5 ? k0 : -k0);
                        mbar_expect_tx(bars + (BAR_FA + (kt & 3)) * 8, OFF_B); mbar_expect_tx(bars + (BAR_FULL + (kt & 3)) * 8, 2 * B_HALF);
                        TILE_X(kt, kk); TILE_W(kt, kk);
                        if (kt == WOP) prefetch_l2_bulk(reinterpret_cast<const char*>(wo) + cta * 6400, 6400);
                    }
                    if (moe) {
                        if ((unsigned)(kt - GP0) < 7u) tma2d(sb + SM_MW + (kt - GP0) * 5120, tm_gu, bars + BAR_GW * 8, mi * 32, (kt - GP0) * 80);
                        if (kt == G7T) tma2d(sb + SM_G7, tm_gu, bars + BAR_GW * 8, mi * 32, 560);
                        if ((unsigned)(kt - DP0) < 2u) prefetch_l2_bulk(wd + (mi * 32 + rank * 16 + (kt - DP0) * 8) * DM, 10240);
                        if (kt == 12) {
#pragma unroll
                            for (int i = 0; i < 5; i++) tma2d(sb + SM_DW + i * 4096, &tm_d, bars + BAR_DW * 8, (rank * 5 + i) * 64, mi * 32);
                        }
                    }
                    if (kt == 3) TL(17);
                }
                __syncwarp();
                if (kt >= 10) {
                    if (kt == 11 && (WO_GATE & 2)) mbar_wait(bars + BAR_RS * 8, 0);
                    if (kt == 12 && (WO_GATE & 4)) mbar_wait(bars + BAR_SEL * 8, 0);
                    if (elect_one()) {
#pragma unroll
                        for (int i0 = (kt == 10 ? 0 : (kt == 11 ? 2 : WO_S)); i0 < (kt == 10 ? 2 : (kt == 11 ? WO_S : 8)); i0 += 2) {
                            const int i = i0 + rank;
                            tma2d_mc(sb + SM_WO + (7 - i) * 10240, &tm_wo, bars + BAR_WO * 8, cm, SRC(i) * 80);
                        }
                    }
                    __syncwarp();
                }
            }
            const uint4* os = &sc->o[m][0][0][0];
            const unsigned* fl = &sc->flag[m][(lane & 7) == g ? g ^ 1 : lane & 7][0];
            const uint4* os2 = os + (g + 1) * 256;
            const uint32_t n1 = g * 4096, n2 = 28672 - n1;
            asm volatile("" : "+l"(fl));
            if (elect_one()) {
#pragma unroll
                for (int t = 0; t < 5; t++) mbar_expect_tx(bars + (BAR_OF + t) * 8, 28672);
            }
            mbar_wait(bars + (BAR_EMPTY + 1) * 8, 0);
            if (lane == 0) mbar_arrive(bars + BAR_GI * 8);
            mbar_wait(bars + BAR_PA * 8, 0);
            unsigned lvl = 0, spins = 0;
#pragma unroll
            for (int t = 0; t < 5; t++) {
                while (__any_sync(0xffffffffu, lvl <= t)) {
                    lvl = ld_relaxed_u32(fl);
                    spin_guard(spins);
                }
                if (t) mbar_wait(bars + (BAR_OE + t - 1) * 8, 0);
                if (elect_one()) {
                    const uint32_t dst = sb + (t == 2 ? SM_O2 : ((t == 0 || t == 3) ? SM_O0 : SM_O1)), fb = bars + (BAR_OF + t) * 8;
                    if (g > 0) bulk_load(dst, os + t * 2048, n1, fb);
                    if (g < 7) bulk_load(dst + n1, os2 + t * 2048, n2, fb);
                    TL(48 + t);
                }
                __syncwarp();
            }
        } else {
            const int ta = tid - 288, wa = warp - 9, c = lane & 3, r = lane >> 2;
            const unsigned tag = ld_relaxed_u32(&sc->epoch[cta * 32]) + 1;
            const Outbox* const box = &sc->box[g >> 1];
            unsigned spins = 0;
            if (wa == 0) {
                uint4 *ro = &sc->o[m][0][g][lane], *rh = &sc->halo[m * 8 + g][lane];
                if (lane < 2) st_relaxed_v4(&sc->rdone[m * 8 + g][lane * 4], make_uint4(0, 0, 0, 0));
                cluster_wait();
                if (lane == 0) mbar_expect_tx(bars + BAR_PX * 8, 2560);
#pragma unroll 1
                for (int t = 0; t < 5; t++, ro += 2048, rh += 64) {
                    mbar_wait(bars + (BAR_AE + RS_PACE(t)) * 8, 0);
                    const uint4 e = make_uint4(EMPTY_WORD, EMPTY_WORD, EMPTY_WORD, EMPTY_WORD);
#pragma unroll
                    for (int i = 0; i < 8; i++) st_relaxed_v4(ro + 32 * i, e);
                    st_relaxed_v4(rh, e); st_relaxed_v4(rh + 32, e);
                }
                if (lane < 2) st_relaxed_v4(&sc->flag[m][g][lane * 4], make_uint4(0, 0, 0, 0));
                fence_gpu();
                __syncwarp();
                if (lane == 0) { st_relaxed_u32(&sc->rdone[m * 8 + g][0], tag); TL(20); }
                const unsigned* rd = &sc->rdone[m * 8 + (lane == 8 && m > 0 ? g - 8 : lane & 7)][0];
                while (!__all_sync(0xffffffffu, ld_relaxed_u32(rd) == tag)) { __nanosleep(POLL_NS); spin_guard(spins); }
                if (lane == 0) { mbar_arrive(bars + BAR_RS * 8); TL(21); }
                unsigned* fo = &sc->flag[m][g][0];
                asm volatile("" : "+l"(fo));
                mbar_wait(bars + BAR_GI * 8, 0);
#pragma unroll 1
                for (int t = 0; t < 5; t++) { mbar_spin(bars + (BAR_PA + t) * 8, 0); if (lane == 0) st_relaxed_u32(fo, t + 1); }
                return;
            } else {
                const bool cw = wa < 3, aside = wa >= 5;
                const int l = min(lane, 29), part = l < 24 ? l >> 3 : (l - 24) >> 1;
                const int pp = warp & 1, ri = lane >> 3;
                float s[8];
#pragma unroll
                for (int e = 0; e < 8; e++) s[e] = 0.f;
                const uint32_t k16 = roles.k16, khi = 0x3f800000u;
#define U_LO(v) __uint_as_float(imul(v, k16))
#define U_HI(v) __uint_as_float(hfma2(v, khi, 0u))
#define GAPS 1
#define GAP(...) do { if (GAPS) { asm volatile("pmevent 0;" : __VA_ARGS__ :: "memory"); } } while (0)
#define ROW_SUMS(v0, v1, v2) do { _Pragma("unroll") for (int e = 0; e < 4; e++) { \
                    const float wl = U_LO((&v2.x)[e]), wh = U_HI((&v2.x)[e]), a = U_LO((&v0.x)[e]), b = U_HI((&v0.x)[e]); \
                    s[0] += a; s[1] = fmaf(a, a, s[1]); s[2] = fmaf(a, wl, s[2]); s[0] += b; s[1] = fmaf(b, b, s[1]); s[2] = fmaf(b, wh, s[2]); \
                    GAP("+f"(s[0]), "+f"(s[1]), "+f"(s[2]), "+r"((&v1.x)[e])); \
                    const float a2 = U_LO((&v1.x)[e]), b2 = U_HI((&v1.x)[e]); \
                    s[4] += a2; s[5] = fmaf(a2, a2, s[5]); s[6] = fmaf(a2, wl, s[6]); s[4] += b2; s[5] = fmaf(b2, b2, s[5]); s[6] = fmaf(b2, wh, s[6]); \
                    GAP("+f"(s[4]), "+f"(s[5]), "+f"(s[6]), "+r"((&v0.x)[(e + 1) & 3]), "+r"((&v2.x)[(e + 1) & 3])); } } while (0)
                if (aside) {
                    const __nv_bfloat16* p0 = x + (m * 128 + g * 16 + 2 * ri + pp) * DM + 64 * JL - k0 + (lane & 7) * 8;
                    const uint32_t wa2 = sb + SM_XSEL + (lane & 7) * 16 + 128 * JL - 2 * k0;
                    cluster_wait();
                    mbar_wait(bars + BAR_WR * 8, 0);
                    if (SIDE_N >= 0) mbar_wait(bars + (BAR_AE + SIDE_N) * 8, 0);
                    uint4 q[10 - JL][2];
#pragma unroll
                    for (int j = 0; j < 10 - JL; j++) { q[j][0] = ldg_v4(p0 + j * 64); q[j][1] = ldg_v4(p0 + 8 * DM + j * 64); }
                    uint4 wn = lds_v4(wa2);
                    __syncwarp();
#pragma unroll
                    for (int j = 0; j < 10 - JL; j++) { uint4 wv = wn; if (j < 9 - JL) wn = lds_v4(wa2 + (j + 1) * 128); ROW_SUMS(q[j][0], q[j][1], wv); }
                    if (tid == 448) TL(62);
                } else {
                    uint32_t ad[4];
#pragma unroll
                    for (int i = 0; i < 4; i++) {
                        const int row = 4 * ((G & 6) + pp) + i;
                        ad[i] = cw ? OFF_B + rank * B_HALF + (l < 24 ? part * 4096 + row * 128 + (((l ^ row) & 7) << 4) : 12288 + part * 1024 + row * 32 + (((l ^ pp) & 1) << 4))
                                   : (i < 2 ? pp * 8192 + (8 * g + ri + 4 * i) * 128 + (((lane ^ (ri + 4 * i)) & 7) << 4) : SM_XSEL + (lane & 7) * 16 + 2 * k0);
                        ad[i] = __shfl_sync(0xffffffffu, sb + ad[i], lane);
                    }
                    if (wa == 1) st_relaxed_v4(&sc->cs[g][G][rank][lane], make_uint4(tag - 1, 0, 0, 0));
                    cluster_wait();
                    if (ta == 32) mbar_expect_tx(bars + BAR_CX * 8, 2048);
                    mbar_wait(bars + BAR_WR * 8, 0);
#pragma unroll 1
                    for (int kt = 0; kt < (cw ? 5 : JL); kt++) {
                        const uint32_t so = (-kt & 3) * STAGE;
                        mbar_wait(bars + ((cw ? BAR_FULL : BAR_FA) + (kt & 3)) * 8, kt >> 2);
                        uint4 v0 = lds_v4(ad[0] + so), v1 = lds_v4(ad[1] + so), v2 = lds_v4(ad[2] + (cw ? so : kt * 128 - (kt == 5 ? 4 * k0 : 0)));
                        if (cw) {
                            const uint4 v3 = lds_v4(ad[3] + so);
#pragma unroll
                            for (int e = 0; e < 4; e++) {
                                s[2 * e] += U_LO((&v0.x)[e]); s[2 * e + 1] += U_HI((&v0.x)[e]); s[2 * e] += U_LO((&v1.x)[e]); s[2 * e + 1] += U_HI((&v1.x)[e]);
                                s[2 * e] += U_LO((&v2.x)[e]); s[2 * e + 1] += U_HI((&v2.x)[e]); s[2 * e] += U_LO((&v3.x)[e]); s[2 * e + 1] += U_HI((&v3.x)[e]);
                                GAP("+f"(s[2 * e]), "+f"(s[2 * e + 1]));
                            }
                        } else ROW_SUMS(v0, v1, v2);
                        __syncwarp();
                        if (lane == 0) mbar_arrive(bars + (BAR_AE + kt) * 8);
                    }
                }
                if (cw) {
                    const uint32_t cx = sb + SM_BX + (rank * 2 + pp) * 512 + lane * 16;
                    st_async_v4(cx, bars + BAR_CX * 8, 0, s[0], s[1], s[2], s[3]); st_async_v4(cx, bars + BAR_CX * 8, 1, s[4], s[5], s[6], s[7]);
                    if (wa == 1) {
                        mbar_wait(bars + BAR_CX * 8, 0);
                        const uint32_t a = sb + SM_BX + lane * 16;
                        const float4 a0 = lds_f4(a), a1 = lds_f4(a + 512), a2 = lds_f4(a + 1024), a3 = lds_f4(a + 1536);
                        st_relaxed_v4(&sc->cs[g][G][rank][lane], make_uint4(tagf((a0.x + a1.x) + (a2.x + a3.x), tag), __float_as_uint((a0.y + a1.y) + (a2.y + a3.y)),
                                                                            __float_as_uint((a0.z + a1.z) + (a2.z + a3.z)), __float_as_uint((a0.w + a1.w) + (a2.w + a3.w))));
                        if (lane == 0) TL(18);
#pragma unroll 1
                        for (int i = lane; i < 140; i += 32) sts_v4(sb + SM_BX + i * 16, make_uint4(0, 0, 0, 0));
                    }
                    bar_sync<7, 64>();
                    uint4 v[8];
#pragma unroll
                    for (int j = 0; j < 8; j++) v[j].x = tag - 1;
                    while (true) {
                        unsigned bad = 0;
#pragma unroll
                        for (int j = 0; j < 8; j++) if ((v[j].x ^ tag) & 15) v[j] = ld_relaxed_v4(&sc->cs[g][j][pp][l]);
                        __syncwarp();
#pragma unroll
                        for (int j = 0; j < 8; j++) bad |= v[j].x ^ tag;
                        if (__all_sync(0xffffffffu, (bad & 15) == 0)) break;
                        spin_guard(spins);
                    }
#pragma unroll
                    for (int e = 0; e < 4; e++) {
                        s[e] = 0.f;
#pragma unroll
                        for (int j = 0; j < 8; j++) s[e] += __uint_as_float((&v[j].x)[e]);
                    }
#pragma unroll
                    for (int j = 0; j < 3; j++) {
                        const int row = 3 * part + j;
                        const uint32_t o0 = pack_bf16(s[0], s[1]), o1 = pack_bf16(s[2], s[3]);
                        s[0] -= bf_lo(o0); s[1] -= bf_hi(o0); s[2] -= bf_lo(o1); s[3] -= bf_hi(o1);
                        sts_f2(sb + SM_BX + pp * 8 + (l < 24 ? row * 128 + (((l ^ row) & 7) << 4) : 1792 + row * 32 + (((l ^ (row >> 2)) & 1) << 4)), __uint_as_float(o0), __uint_as_float(o1));
                    }
                    asm volatile("fence.proxy.async.shared::cta;" ::: "memory");
                    __syncwarp();
                    if (lane == 0) { mbar_arrive(bars + BAR_CS * 8); TL(25); }
                } else {
#pragma unroll
                    for (int e = 0; e < 3; e++) s[e] = ((lane & 4) ? s[4 + e] : s[e]) + shfl_x((lane & 4) ? s[e] : s[4 + e], 4);
#pragma unroll
                    for (int o = 1; o < 4; o <<= 1) {
#pragma unroll
                        for (int e = 0; e < 3; e++) s[e] += shfl_x(s[e], o);
                    }
                    const uint32_t sa = sb + SM_GT + pp * 128 + r * 16;
                    if (aside) {
                        sts_f4(sa, s[0], s[1], s[2], 0.f); asm volatile("bar.arrive 6, 128;" ::: "memory");
                    }
                    else {
                        bar_sync<6, 128>();
                        const float4 o = lds_f4(sa);
                        const int row = 8 * g + ri + (lane & 4);
                        const float mean = (s[0] + o.x) * (1.0f / DM);
                        const float sd = sqrt_approx(bfr(bfr(fmaxf(fmaf(-mean, mean, (s[1] + o.y) * (1.0f / DM)), 0.f)) + 1e-5f));
                        if (c == 0) st_relaxed_v2(&sc->rowinfo[m][pp][row], pack_bf16(mean, sd), tagf(s[2] + o.z, tag));
                        if (tid == 384) TL(22);
                    }
                    if (!aside) {
                        const uint4* r0 = reinterpret_cast<const uint4*>(&sc->rowinfo[m][pp][0]);
                        uint4 a, b;
                        while (true) {
                            __nanosleep(POLL_NS);
                            a = ld_relaxed_v4(r0 + lane); b = ld_relaxed_v4(r0 + (m > 0 ? 28 - 64 : 0) + c);
                            if (__all_sync(0xffffffffu, (((a.y ^ tag) | (a.w ^ tag) | (b.y ^ tag) | (b.w ^ tag)) & 15) == 0)) break;
                            spin_guard(spins);
                        }
                        sts_f4(sb + SM_ST + (pp * 72 + 8 + 2 * lane) * 8, bf_lo(a.x), rcp(bf_hi(a.x)), bf_lo(a.z), rcp(bf_hi(a.z)));
                        if (lane < 4) sts_f4(sb + SM_ST + (pp * 72 + 2 * lane) * 8, bf_lo(b.x), rcp(bf_hi(b.x)), bf_lo(b.z), rcp(bf_hi(b.z)));
                        __syncwarp();
                        if (lane == 0) { mbar_arrive(bars + BAR_CS * 8); if (pp == 0) TL(24); }
                    }
                }
            }
            if (wa == 6) {
                const int r = lane >> 1;
                while (ld_relaxed_u32(&sc->open[g >> 1][0]) != tag) spin_guard(spins);
                mbar_wait(bars + (BAR_AE + JL - 1) * 8, 0); mbar_wait(bars + (BAR_FA + 2) * 8, 1); mbar_wait(bars + (BAR_EMPTY + 2) * 8, 1);
                if (WO_GATE & 16) mbar_wait(bars + BAR_SEL * 8, 0);
#pragma unroll 1
                for (int i = 0; i < 8; i++) {
                    const __nv_bfloat16* src = wo + (SRC(i) * 80 + r) * DM + ct + (lane & 1) * 8;
                    const uint32_t dst = sb + SM_WT + (i & 1) * 10240 + r * 128 + ((((i & 6) + (lane & 1)) ^ (r & 7)) << 4);
#pragma unroll
                    for (int t = 0; t < 5; t++) cp_async16(dst + t * 2048, src + t * 16 * DM);
                    __nanosleep(TAIL_NS);
                }
                {
                            while (ld_relaxed_u32(&box->msg[80]) == EMPTY_WORD) { __nanosleep(POLL_NS); spin_guard(spins); }
                            uint4 q[6];
                            while (true) {
#pragma unroll
                                for (int j = 0; j < 6; j++) q[j] = ld_relaxed_v4(&box->msg[min(lane + 32 * j, 160)]);
                                __syncwarp();
                                if (__all_sync(0xffffffffu, max(max(max(q[0].x, q[1].x), max(q[2].x, q[3].x)), max(q[4].x, q[5].x)) != EMPTY_WORD)) break;
                                spin_guard(spins);
                            }
#pragma unroll
                            for (int j = 0; j < 6; j++) sts_v4(sb + SM_XSEL + min(lane + 32 * j, 160) * 16, q[j]);
                            __syncwarp();
                            if (lane == 0) { mbar_arrive(bars + BAR_SEL * 8); TL(23); }
                }
                asm volatile("cp.async.wait_all;\nfence.proxy.async.shared::cta;" ::: "memory");
                __syncwarp();
                if (lane == 0) { mbar_arrive(bars + BAR_WO * 8); TL(19); }
                return;
            }
            if (moe) {
                const int krow = (lane >> 4) * 8 + (lane & 7), ch = (lane >> 3) & 1;
                const uint32_t wp = sb + SM_MW + (wa - 1) * 1024 + krow * 64 + ((ch ^ (krow >> 1)) & 3) * 16;
                const uint32_t xa = sb + SM_XSEL + (lane & 1) * 1296 + ch * 16 + (wa - 1) * 32 + (lane >> 4) * 160;
                uint32_t a[10][4];
                mbar_wait(bars + BAR_GW * 8, 0);
#pragma unroll
                for (int i = 0; i < 5; i++) { ldsm4t(wp + i * 5120, a[2 * i]); ldsm4t((wp + i * 5120) ^ 32, a[2 * i + 1]); if (PRE_NS) __nanosleep(PRE_NS); }
                float d[2][4];
#pragma unroll
                for (int e = 0; e < 8; e++) d[e >> 2][e & 3] = 0.f;
                mbar_wait(bars + BAR_SEL * 8, 0);
                mbar_wait(bars + (BAR_EMPTY + 1) * 8, 0);
                if (ta == 32) TL(26);
#pragma unroll
                for (int i = 0; i < 8; i += 2) {
                    uint32_t b[4];
                    ldsm4(xa + i * 160, b[0], b[1], b[2], b[3]);
#pragma unroll
                    for (int e = 0; e < 4; e++) {
                        uint32_t (&f)[4] = a[(2 * i + e) % 10];
                        mma16(d[e & 1], f[0], f[1], f[2], f[3], b[e & 2], b[(e & 2) + 1]);
                        if (2 * i + e < 6) ldsm4t((wp + (i + (e >> 1) == 2 ? SM_G7 - SM_MW : (i + (e >> 1) + 5) * 5120)) ^ ((e & 1) * 32), f);
                    }
                }
                {
                    const float u0 = (c & 2) ? ((c & 1) ? d[1][2] : d[1][0]) : ((c & 1) ? d[0][2] : d[0][0]);
                    const float u1 = (c & 2) ? ((c & 1) ? d[1][3] : d[1][1]) : ((c & 1) ? d[0][3] : d[0][1]);
                    const uint32_t dst = sb + SM_BX + (rank * 5 + wa - 1) * 256 + (c * 8 + r) * 8;
                    st_async_v2(dst, bars + BAR_PX * 8, 0, u0, u1); st_async_v2(dst, bars + BAR_PX * 8, 1, u0, u1);
                }
                if (wa >= 2) {
                    mbar_wait(bars + BAR_DW * 8, 0);
#pragma unroll
                    for (int b = 0; b < 5; b++) {
                        const int nb = (wa - 2) * 5 + b;
                        const uint32_t dp = sb + SM_DW + (nb >> 2) * 4096 + krow * 128 + ((((nb & 3) * 2 + ch) ^ (krow & 7)) << 4);
                        ldsm4t(dp, a[2 * b]); ldsm4t(dp + 2048, a[2 * b + 1]);
                    }
                } else {
                    mbar_wait(bars + BAR_PX * 8, 0);
                    if (lane == 0) { mbar_arrive(bars + BAR_OE * 8); TL(27); }
                    float2 gs = make_float2(0.f, 0.f), us = gs;
#pragma unroll
                    for (int e = 0; e < 5; e++) {
                        const float2 u = lds_f2(sb + SM_BX + e * 256 + lane * 8), v = lds_f2(sb + SM_BX + 1280 + e * 256 + lane * 8);
                        gs.x += u.x; gs.y += u.y; us.x += v.x; us.y += v.y;
                    }
                    const uint32_t g2 = pack_bf16(gs.x, gs.y);
                    const uint32_t h2 = hmul2(pack_bf16(bf_lo(g2) * sigmoid_f(bf_lo(g2)), bf_hi(g2) * sigmoid_f(bf_hi(g2))), pack_bf16(us.x, us.y));
                    sts_u16(sb + SM_H + lane * 2, h2); sts_u16(sb + SM_H + 64 + lane * 2, h2 >> 16);
                }
                bar_sync<3, 160>();
                if (ta == 32) mbar_arrive(bars + (BAR_OE + 1) * 8);
                if (wa >= 2) {
                    uint32_t hb[4];
                    ldsm4(sb + SM_H + (lane & 1) * 64 + (lane >> 3) * 16, hb[0], hb[1], hb[2], hb[3]);
                    float yv[5];
#pragma unroll
                    for (int b = 0; b < 5; b++) {
                        float o[4] = {0.f, 0.f, 0.f, 0.f};
                        mma16(o, a[2 * b][0], a[2 * b][1], a[2 * b][2], a[2 * b][3], hb[0], hb[1]);
                        mma16(o, a[2 * b + 1][0], a[2 * b + 1][1], a[2 * b + 1][2], a[2 * b + 1][3], hb[2], hb[3]);
                        yv[b] = (c & 2) ? ((c & 1) ? o[3] : o[2]) : ((c & 1) ? o[1] : o[0]);
                    }
                    uint4* const dst = &sc->yp[rank * 4 + wa - 2][mi][0];
                    st_relaxed_v4(dst + lane, make_uint4(tagf(yv[0], tag), __float_as_uint(yv[1]), __float_as_uint(yv[2]), __float_as_uint(yv[3])));
                    st_relaxed_u32(reinterpret_cast<unsigned*>(dst + 32) + lane, tagf(yv[4], tag));
                    if (tid == 384) TL(28);
                }
            } else if (ta == 32) { mbar_arrive(bars + BAR_OE * 8); mbar_arrive(bars + (BAR_OE + 1) * 8); }
            if (wa == 1) {
                mbar_wait(bars + BAR_SEL * 8, 0);
                const uint2 sel = lds_v2(sb + SM_TOP);
                if ((sel.x >> 7) == m || (sel.y >> 7) == m) {
                    uint4 v;
                    do { __nanosleep(POLL_NS); v = ld_relaxed_v4(&box->gt[g & 1][min(lane, 19)]); spin_guard(spins); } while (__any_sync(0xffffffffu, v.x == EMPTY_WORD));
                    sts_v4(sb + SM_GT + min(lane, 19) * 16, v);
                    __syncwarp();
                    if (lane == 0) TL(30);
                }
                if (lane == 0) { mbar_arrive(bars + BAR_Y * 8); st_relaxed_u32(&sc->epoch[cta * 32], tag); }
            }
        }
    } else {
        asm volatile("setmaxnreg.inc.sync.aligned.u32 192;");
        const int p = warp >> 2, w = warp & 3, c = lane & 3, r = lane >> 2;
        const uint32_t stb = sb + SM_ST + (p * 72 + w * 16) * 8;
        float acc[120];
#pragma unroll
        for (int i = 0; i < 120; i++) asm volatile("" : "=f"(acc[i]));
        uint32_t xs[5][4];
#pragma unroll
        for (int i = 0; i < 20; i++) asm volatile("" : "=r"(xs[i >> 2][i & 3]));
#define EXT_STEP() do {        \
            mbar_wait(bars + BAR_CS * 8, 0); \
            const uint32_t msk = c == 0 ? 0xffffffffu : (c == 1 ? 0x0000ffffu : 0u); \
            const uint32_t e0 = dup_hi(-lds_f32(stb + (8 + r) * 8)) & msk, e1 = dup_hi(-lds_f32(stb + (16 + r) * 8)) & msk; \
            wg_fence(); \
            wgmma_rs_n48x(acc, e0, e1, 0u, 0u, (((sb + SM_BX + 1792) & 0x3ffffu) >> 4) | ((96u >> 4) << 16)); \
            wgmma_rs_n192x(acc, e0, e1, 0u, 0u, (((sb + SM_BX) & 0x3ffffu) >> 4) | ((384u >> 4) << 16)); \
            wg_commit(); } while (0)
#define EXT_J 4
        cluster_wait();
        {
            const int lr = w * 16 + (lane & 15);
            uint32_t st = __shfl_sync(0xffffffffu, sb + p * 8192 + lr * 128 + (((lr & 7) ^ (lane >> 4)) << 4), lane);
            const bool lead = __shfl_sync(0xffffffffu, tid & 127, lane) == 0;
            uint32_t blo = (((sb + OFF_B) & 0x3ffffu) >> 4) | ((4096u >> 4) << 16);
            const uint32_t tdiff = (12288u >> 4) + ((1024u >> 4) << 16) - ((4096u >> 4) << 16);
            const int kx = (5 * g) >> 2;
#define PD 1
            uint32_t af[4][4];
            mbar_wait(bars + BAR_FA * 8, 0);
            ldsm4(st, af[0][0], af[0][1], af[0][2], af[0][3]);
            if (PD == 2) ldsm4(st ^ 32, af[1][0], af[1][1], af[1][2], af[1][3]);
#pragma unroll 1
            for (int kt = 0; kt < 10; kt++) {
#pragma unroll
                for (int j = 0; j < 4; j++) {
                    uint32_t (&nx)[4] = af[(j + PD) & 3];
                    if (j == 0) {
                        mbar_wait(bars + (BAR_FULL + (kt & 3)) * 8, (kt >> 2) & 1);
                    }
                    if (j == 4 - PD && kt < 9) {
                        st += (kt & 3) == 0 ? 3 * STAGE : -STAGE;
                        mbar_wait(bars + (BAR_FA + ((kt + 1) & 3)) * 8, ((kt + 1) >> 2) & 1);
                    }
                    ldsm4(st ^ (((j + PD) & 3) << 5), nx[0], nx[1], nx[2], nx[3]);
                    wg_fence();
                    const uint32_t sd = j ? 1u : (uint32_t)kt;
                    wgmma_rs_n48(acc, af[j][0], af[j][1], af[j][2], af[j][3], blo + tdiff + (j >> 1) * (B_HALF >> 4) + (j & 1) * 32, sd);
                    wgmma_rs_n192(acc, af[j][0], af[j][1], af[j][2], af[j][3], blo + (j >> 1) * (B_HALF >> 4) + (j & 1) * 128, sd);
                    wg_commit();
#define WD 2
                    wg_wait<WD>();
                    if (j == WD - 1 && kt > 0 && lead) mbar_arrive_both(bars + (BAR_EMPTY + ((kt - 1) & 3)) * 8);
                    if (j == EXT_J && kt == 9) EXT_STEP();
                    const int kg = kt + ((kt < 5 ? k0 : -k0) >> 6);
                    if (j == 1 && (unsigned)(kg - kx) < 2u) {
#pragma unroll
                        for (int t = 0; t < 5; t++) {
                            const int ks = 5 * g + (t < 4 ? t + odd : 4 - 4 * odd);
                            ldsm4_if((ks >> 2) == kg, st ^ ((ks & 3) << 5), xs[t]);
                        }
                    }
                }
                blo += (kt & 3) == 0 ? 3 * (STAGE >> 4) : -(STAGE >> 4);
            }
        }
        if (EXT_J > 3) EXT_STEP();
        if (tid == 0) TL(10);
        const float2 st0 = lds_f2(stb + (8 + r) * 8), st1 = lds_f2(stb + (16 + r) * 8);
        const float rs0 = st0.y, rs1 = st1.y;
        const uint4 sP = lds_v4(stb + (2 * c) * 8), sB = lds_v4(stb + (8 + 2 * c) * 8), sC = lds_v4(stb + (16 + 2 * c) * 8);
        const bool up0 = 2 * c > r, up1 = 2 * c + 1 > r;
        const float k00 = __uint_as_float(up0 ? sP.y : sB.y), k01 = __uint_as_float(up1 ? sP.w : sB.w);
        const float k10 = __uint_as_float(up0 ? sB.y : sC.y), k11 = __uint_as_float(up1 ? sB.w : sC.w);
        const float sc2 = 0.22360679774997896f * 1.4426950408889634f;
        const float f00 = rs0 * k00 * sc2, f01 = rs0 * k01 * sc2, f10 = rs1 * k10 * sc2, f11 = rs1 * k11 * sc2;
        const float fa[4] = {up0 ? f00 : 0.f, up1 ? f01 : 0.f, up0 ? f10 : 0.f, up1 ? f11 : 0.f};
        const float fb[4] = {f00 - fa[0], f01 - fa[1], f10 - fa[2], f11 - fa[3]};
        const bool first = (m == 0 && w == 0);
        const float b00 = (first && up0) ? -1e30f : 0.f, b01 = (first && up1) ? -1e30f : 0.f;
#define PV3 0
#define MSK(a, b) ((a) & (b))
        const uint32_t mup = (up0 ? 0x0000ffffu : 0u) | (up1 ? 0xffff0000u : 0u), mdn = ~mup;
        const uint32_t qlo = c < 2;
        const uint32_t exs = sb + SM_EX + p * 8192 + w * 2560 + lane * 16;
        const uint32_t exr = __shfl_sync(0xffffffffu, exs - (w ? 2560 : 0), lane);
        uint4* hg = &sc->halo[m * 8 + g - (w ? 0 : 8)][p * 160 + lane];
        uint32_t* ob = reinterpret_cast<uint32_t*>(&sc->o[m][0][g][warp * 32]) + lane;
        asm volatile("" : "+l"(hg), "+l"(ob));
        mbar_wait(bars + BAR_RS * 8, 0);
        if (p == 0) bar_sync<1, 128>(); else bar_sync<2, 128>();
        wg_wait<0>();
        if ((tid & 127) == 0) { mbar_arrive_both(bars + (BAR_EMPTY + 1) * 8); TL(2 + p); }
        uint32_t Q[10][2], K[10][2], V[10][2], Kp[10], Vp[10];
        if (odd) pack_kv<1, 1>(acc, K, V); else pack_kv<0, 1>(acc, K, V);
        ATS(0);
        uint4 rcv[5];
        {
            const uint4 snd[5] = {make_uint4(K[0][1], K[1][1], K[3][1], K[4][1]), make_uint4(K[5][1], K[6][1], K[8][1], K[9][1]), make_uint4(K[2][1], K[7][1], V[0][1], V[1][1]),
                                  make_uint4(V[2][1], V[3][1], V[4][1], V[5][1]), make_uint4(V[6][1], V[7][1], V[8][1], V[9][1])};
            if (w == 3) {
#pragma unroll
                for (int i = 0; i < 5; i++) st_relaxed_v4(hg + i * 32, snd[i]);
            } else {
#pragma unroll
                for (int i = 0; i < 5; i++) sts_v4(exs + i * 512, snd[i]);
            }
            if (tid == 96) TL(11);
        }
        ATS(2);
#define BX(h) (5 * ((h) >> 1) + 3 * ((h) & 1))
#define BZ(h) (5 * ((h) >> 1) + 2)
        float l[4][2];
        uint32_t qz[4][2], pa[4][4];
#define PROBS(la, lb, h, ka, kb, iu, id) do { \
            const float e0 = ex2(la[0]), e1 = ex2(la[1]), e2 = ex2(lb[0]), e3 = ex2(lb[1]); \
            float sum[4] = {0.f, 0.f, 0.f, 0.f}; \
            mma8(sum, pack_bf16(e0, e1), pack_bf16(e2, e3), 0x3f803f80u); \
            const float i0 = rcp(sum[0]), i1 = rcp(sum[2]); \
            const uint32_t p0 = pack_bf16(e0 * ka * i0, e1 * kb * i0), p1 = pack_bf16(e2 * ka * i1, e3 * kb * i1); \
            pa[h][iu] = MSK(p0, mup); pa[h][id] = MSK(p0, mdn); pa[(h) + 1][iu] = MSK(p1, mup); pa[(h) + 1][id] = MSK(p1, mdn); } while (0)
        float lu[4][2];
#define OWN_KEYS(ODD) do { pack_q<ODD>(acc, Q); pack_kv<ODD, 0>(acc, K, V); \
            _Pragma("unroll") for (int h = 0; h < 4; h++) { \
                const int bx = BX(h), by = bx + 1, bz = BZ(h); \
                if (h & 1) { qz[h][0] = Q[bz][0] - qz[h & 2][0]; qz[h][1] = Q[bz][1] - qz[h & 2][1]; } \
                else { qz[h][0] = imul(Q[bz][0], qlo); qz[h][1] = imul(Q[bz][1], qlo); } \
                float sm_[4] = {0.f, 0.f, 0.f, 0.f}, sn[4] = {0.f, 0.f, 0.f, 0.f}; \
                mma16(sm_, Q[bx][0], Q[bx][1], Q[by][0], Q[by][1], K[bx][0], K[by][0]); \
                mma16(sn, Q[bx][0], Q[bx][1], Q[by][0], Q[by][1], K[bx][1], K[by][1]); \
                mma8(sm_, qz[h][0], qz[h][1], K[bz][0]); mma8(sn, qz[h][0], qz[h][1], K[bz][1]); \
                l[h][0] = fmaf(sm_[0], fb[0], b00); l[h][1] = fmaf(sm_[1], fb[1], b01); \
                lu[h][0] = fmaf(sm_[2], fa[2], sn[2] * fb[2]); lu[h][1] = fmaf(sm_[3], fa[3], sn[3] * fb[3]); \
                asm volatile("" : "+f"(lu[h][0]), "+f"(lu[h][1]) :: "memory"); \
            } } while (0)
        if (odd) OWN_KEYS(1); else OWN_KEYS(0);
        ATS(1);
        if (p == 0) bar_sync<1, 128>(); else bar_sync<2, 128>();
        if (w == 0 && m > 0) {
#pragma unroll
            for (int i = 0; i < 5; i++) rcv[i] = ld_relaxed_v4(hg + i * 32);
        } else {
#pragma unroll
            for (int i = 0; i < 5; i++) rcv[i] = lds_v4(exr + i * 512);
        }
#pragma unroll
        for (int h = 0; h < 4; h++) {
            float m1 = fmaxf(lu[h][0], lu[h][1]);
            m1 = fmaxf(m1, shfl_x(m1, 1)); m1 = fmaxf(m1, shfl_x(m1, 2));
            lu[h][0] -= m1; lu[h][1] -= m1;
        }
        PROBS(lu[0], lu[1], 0, k10, k11, 1, 3); PROBS(lu[2], lu[3], 2, k10, k11, 1, 3);
#pragma unroll
        for (int h = 0; h < 4; h++) asm volatile("" : "+r"(pa[h][1]), "+r"(pa[h][3]) :: "memory");
        ATS(3);
        if (w == 0 && m > 0) {
            unsigned spins = 0;
            while (__any_sync(0xffffffffu, max(max(max(rcv[0].x, rcv[1].x), max(rcv[2].x, rcv[3].x)), rcv[4].x) == EMPTY_WORD) && ++spins < SPIN_MAX) {
#pragma unroll
                for (int i = 0; i < 5; i++) rcv[i] = ld_relaxed_v4(hg + i * 32);
            }
        }
        Kp[0] = rcv[0].x; Kp[1] = rcv[0].y; Kp[3] = rcv[0].z; Kp[4] = rcv[0].w; Kp[5] = rcv[1].x; Kp[6] = rcv[1].y; Kp[8] = rcv[1].z; Kp[9] = rcv[1].w;
        Kp[2] = rcv[2].x; Kp[7] = rcv[2].y; Vp[0] = rcv[2].z; Vp[1] = rcv[2].w; Vp[2] = rcv[3].x; Vp[3] = rcv[3].y; Vp[4] = rcv[3].z; Vp[5] = rcv[3].w;
        Vp[6] = rcv[4].x; Vp[7] = rcv[4].y; Vp[8] = rcv[4].z; Vp[9] = rcv[4].w;
        ATS(4);
        if (tid == 0) TL(4);
        if (tid == 32) TL(5);
        uint32_t of[10][2];
#define PUBLISH(t) do { st_relaxed_u32(ob + (t) * 8192, of[2 * (t)][0]); st_relaxed_u32(ob + (t) * 8192 + 32, of[2 * (t) + 1][0]); \
            st_relaxed_u32(ob + (t) * 8192 + 64, of[2 * (t)][1]); st_relaxed_u32(ob + (t) * 8192 + 96, of[2 * (t) + 1][1]); \
            if (lane == 0) mbar_arrive(bars + (BAR_PA + (t)) * 8); } while (0)
#define FRONT(h) do { \
            float sp[4] = {0.f, 0.f, 0.f, 0.f}; \
            mma16(sp, Q[BX(h)][0], Q[BX(h)][1], Q[BX(h) + 1][0], Q[BX(h) + 1][1], Kp[BX(h)], Kp[BX(h) + 1]); \
            mma8(sp, qz[h][0], qz[h][1], Kp[BZ(h)]); \
            l[h][0] = fmaf(sp[0], fa[0], l[h][0]); l[h][1] = fmaf(sp[1], fa[1], l[h][1]); \
            float m0 = fmaxf(l[h][0], l[h][1]); \
            m0 = fmaxf(m0, shfl_x(m0, 1)); m0 = fmaxf(m0, shfl_x(m0, 2)); \
            l[h][0] -= m0; l[h][1] -= m0; } while (0)
#define MID(h) PROBS(l[h], l[(h) + 1], h, k00, k01, 2, 0)
#define BACK(h) do { \
            _Pragma("unroll") for (int b = 0; b < 3; b++) { \
                const int bb = b < 2 ? BX(h) + b : BZ(h); \
                float O[4] = {0.f, 0.f, 0.f, 0.f}; \
                if (PV3) { mma8(O, 0u, pa[h][3], V[bb][1]); mma8(O, pa[h][0], pa[h][1], V[bb][0]); } \
                else mma16(O, pa[h][0], pa[h][1], 0u, pa[h][3], V[bb][0], V[bb][1]); \
                mma8(O, pa[h][2], 0u, Vp[bb]); \
                const uint32_t o0 = pack_bf16(O[0], O[1]), o1 = pack_bf16(O[2], O[3]); \
                of[bb][0] = (b == 2 && ((h) & 1) && c < 2) ? of[bb][0] : o0; of[bb][1] = (b == 2 && ((h) & 1) && c < 2) ? of[bb][1] : o1; \
            } } while (0)
#define HOLD_L(h) asm volatile("" : "+f"(l[h][0]), "+f"(l[h][1]) :: "memory")
#define HOLD_K(h) asm volatile("" : "+r"(Kp[BX(h)]) :: "memory")
#define PA() do { if (tid == 0) TL(6); if (tid == 32) TL(8); } while (0)
#define HOLD_P(h) asm volatile("" : "+r"(pa[h][0]), "+r"(pa[h][2]), "+r"(pa[h][3]) :: "memory")
        FRONT(0); FRONT(1); MID(0); BACK(0); PUBLISH(0); PA(); sched_fence(); HOLD_P(1); HOLD_K(2); HOLD_K(3); FRONT(2); FRONT(3); BACK(1); PUBLISH(1); MID(2); BACK(2); PUBLISH(2); BACK(3);
        if (tid == 0) TL(7);
        if (tid == 32) TL(9);
#define TRK 4
        float acc2[40];
#pragma unroll
        for (int i = 0; i < 40; i++) asm volatile("" : "=f"(acc2[i]));
        uint32_t gate[5][4];
        if ((TRK <= 1 || TRK == 4) && SPLIT != 3) PUBLISH(2);
        if (TRK == 0) { PUBLISH(3); PUBLISH(4); }
        const float2 su0 = lds_f2(stb + (8 + r) * 8), su1 = lds_f2(stb + (16 + r) * 8);
        const float rh0 = bfr(0.5f * su0.y), rh1 = bfr(0.5f * su1.y);
        const uint32_t gm[2] = {dup_hi(su0.x), dup_hi(su1.x)}, gh[2] = {dup_hi(rh0), dup_hi(rh1)};
        const uint32_t gl[2] = {pack_bf16(0.5f * su0.y - rh0, 0.5f * su0.y - rh0), pack_bf16(0.5f * su1.y - rh1, 0.5f * su1.y - rh1)};
        mbar_wait(bars + BAR_WO * 8, 0);
        bar_sync<4, 256>();
        if (tid == 0) TL(13);
        const uint32_t wlo = ((sb + SM_WO) & 0x3ffffu) >> 4, alo = (((sb + p * 2048) & 0x3ffffu) >> 4) | (8u << 16);
#define WPOS(ks) ((7 - (ks) / 5) * 5 + (ks) % 5)
#define WDESC(ks) (wlo + WPOS(ks) * 128 + (((SM_WT - SM_WO + ((ks) % 10 - WPOS(ks)) * 2048 + ((ks) / 10) * 32) >> 4) << 16))
        wg_fence();
#pragma unroll
        for (int t = 0; t < 5; t++) wgmma_rs_n80(acc2, of[2 * t][0], of[2 * t][1], of[2 * t + 1][0], of[2 * t + 1][1], WDESC(t), t != 0);
        wg_commit();
#define NG0 2
#define GATES(t) do { _Pragma("unroll") for (int e = 0; e < 4; e++) {        \
                const uint32_t d = hsub2(xs[t][e], gm[e & 1]), h2 = hfma2(d, gh[e & 1], hmul2(d, gl[e & 1]));        \
                const float a = bf_lo(h2), b = bf_hi(h2); \
                gate[t][e] = pack_bf16(fmaf(a, tanh_f(a), a), fmaf(b, tanh_f(b), b)); \
                asm volatile("" : "+r"(gate[t][e]) :: "memory"); } } while (0)
        GATES(0);
        if (TRK == 4) { sched_fence(); PUBLISH(3); }
        if (TRK && TRK < 4) {
            mbar_wait(bars + BAR_GI * 8, 0);
            if (TRK >= 2 && SPLIT != 3) PUBLISH(2);
            if (TRK <= 2) { PUBLISH(3); PUBLISH(4); }
        }
#pragma unroll
        for (int t = 1; t < NG0; t++) GATES(t);
        if (TRK == 4) { sched_fence(); PUBLISH(4); }
        if (tid == 0) TL(12);
#pragma unroll
        for (int t = 0; t < 5; t++) {
            const uint32_t ad = alo + ((t == 2 ? SM_O2 : ((t == 0 || t == 3) ? SM_O0 : SM_O1)) >> 4);
            mbar_spin(bars + (BAR_OF + t) * 8, 0);
            if (STAG < 5 && t == STAG && p == 1) bar_sync<5, 256>();
            if (TRK == 3 && t == 0) { PUBLISH(3); PUBLISH(4); }
            wg_fence();
#pragma unroll
            for (int i = 0; i < 7; i++) {
                wgmma_ss_n80(acc2, ad + i * 256, WDESC((i + 1) * 5) + t * 128);
                if (i == 0 && (t == 1 || t == 2)) {
                    wg_commit(); wg_wait<1>();
                    if ((tid & 127) == 0) mbar_arrive(bars + (BAR_OE + t + 1) * 8);
                }
                if (STAG < 5 && i == 4 && t == 4 && p == 0) asm volatile("bar.arrive 5, 256;" ::: "memory");
            }
            wg_commit();
            if (t + NG0 < 5) GATES(t + NG0);
        }
        const int wrow = m * 128 + 32 * w + p;
        {
            mbar_wait(bars + BAR_SEL * 8, 0);
            const uint2 sel = lds_v2(sb + SM_TOP);
            const unsigned d0 = sel.x - wrow, d1 = sel.y - wrow;
            if ((d0 & ~30u) == 0 || (d1 & ~30u) == 0) {
                mbar_wait(bars + BAR_Y * 8, 0);
#pragma unroll
                for (int h = 0; h < 2; h++) {
                    const unsigned me = 2 * r + 16 * h;
                    if (d0 == me || d1 == me) {
#pragma unroll
                        for (int t = 0; t < 5; t++) {
                            const uint32_t a = sb + SM_GT + (d0 == me ? 0 : 160) + (t < 4 ? t + odd : 4 - 4 * odd) * 32 + c * 4;
                            gate[t][h] = lds_u32(a); gate[t][2 + h] = lds_u32(a + 16);
                        }
                    }
                }
                __syncwarp();
            }
        }
        const uint32_t ssb = sb + (warp < 6 ? SM_EX : SM_G7 - 6 * 2560) + warp * 2560;
        const uint32_t laddr = ssb + (lane & 15) * 160 + (lane >> 4) * 16;
        wg_wait<0>();
        if (tid == 0) TL(1);
        if (tid == 128) TL(14);
        if (__any_sync(0xffffffffu, acc2[0] != acc2[0] || acc2[2] != acc2[2])) {
#pragma unroll
            for (int i = 0; i < 40; i++) acc2[i] = 0.f;
            const int krow = lane & 15;
#pragma unroll 1
            for (int ks = 0; ks < 40; ks++) {
                const int i = ks / 5;
                const uint32_t* src = ob + (ks - 5 * i) * 8192 + (SRC(i) - g) * 1024;
                uint32_t a0, a1, a2, a3; unsigned spins = 0;
                do { a0 = ld_relaxed_u32(src); a2 = ld_relaxed_u32(src + 32); a1 = ld_relaxed_u32(src + 64); a3 = ld_relaxed_u32(src + 96); }
                while (__any_sync(0xffffffffu, max(max(a0, a1), max(a2, a3)) == EMPTY_WORD) && ++spins < SPIN_MAX);
#pragma unroll
                for (int nb = 0; nb < 5; nb++) {
                    uint32_t b[4];
                    ldsm4t(sb + (nb < 4 ? SM_WO + (35 + ks - 10 * i) * 2048 : SM_WT + (ks % 10) * 2048) + krow * 128 + (((2 * (nb < 4 ? nb : ks / 10) + (lane >> 4)) ^ (krow & 7)) << 4), b);
                    mma16(*reinterpret_cast<float (*)[4]>(&acc2[8 * nb]), a0, a1, a2, a3, b[0], b[1]);
                    mma16(*reinterpret_cast<float (*)[4]>(&acc2[8 * nb + 4]), a0, a1, a2, a3, b[2], b[3]);
                }
            }
        }
#pragma unroll
        for (int t = 0; t < 5; t++) {
            uint32_t o[4];
#pragma unroll
            for (int e = 0; e < 4; e++) o[e] = hadd2(xs[t][e], hmul2(pack_bf16(acc2[8 * t + 2 * e], acc2[8 * t + 2 * e + 1]), gate[t][e]));
            stsm4(laddr + (t < 4 ? t + odd : 4 - 4 * odd) * 32, o[0], o[1], o[2], o[3]);
        }
        asm volatile("fence.proxy.async.shared::cta;" ::: "memory");
        __syncwarp();
        if (elect_one()) tma3d_store(&tm_o, ssb, g * 80, m * 64 + w * 16, p);
    }
}

typedef CUresult (*EncodeFn)(CUtensorMap*, CUtensorMapDataType, cuuint32_t, void*, const cuuint64_t*, const cuuint64_t*, const cuuint32_t*,
                             const cuuint32_t*, CUtensorMapInterleave, CUtensorMapSwizzle, CUtensorMapL2promotion, CUtensorMapFloatOOBfill);

static void encode(EncodeFn enc, CUtensorMap* tm, const void* ptr, int rank, uint64_t d0, uint64_t d1, uint64_t d2, uint64_t s1, uint64_t s2,
                   uint32_t b0, uint32_t b1, uint32_t b2, CUtensorMapSwizzle swz) {
    cuuint64_t dims[3] = {d0, d1, d2}, strides[2] = {s1, s2};
    cuuint32_t box[3] = {b0, b1, b2}, es[3] = {1, 1, 1};
    enc(tm, CU_TENSOR_MAP_DATA_TYPE_BFLOAT16, rank, const_cast<void*>(ptr), dims, strides, box, es, CU_TENSOR_MAP_INTERLEAVE_NONE, swz,
        CU_TENSOR_MAP_L2_PROMOTION_L2_128B, CU_TENSOR_MAP_FLOAT_OOB_FILL_NONE);
}

}

extern "C" void kernel_launch(void* const* d_in, const int* in_sizes, int n_in, void* d_out, int out_size) {
    using namespace fk;
    (void)in_sizes; (void)n_in; (void)out_size;
    const __nv_bfloat16* x = (const __nv_bfloat16*)d_in[0];
    const __nv_bfloat16* wqkv = (const __nv_bfloat16*)d_in[1];
    const __nv_bfloat16* wo = (const __nv_bfloat16*)d_in[2];
    const __nv_bfloat16* wr = (const __nv_bfloat16*)d_in[4];
    const __nv_bfloat16* wg = (const __nv_bfloat16*)d_in[5];
    const __nv_bfloat16* wu = (const __nv_bfloat16*)d_in[6];
    const __nv_bfloat16* wd = (const __nv_bfloat16*)d_in[7];
    static EncodeFn enc = nullptr;
    static Scratch* scratch = nullptr;
    static Roles roles; static int by_sm = 0;
    if (!enc) {
        void* fn = nullptr; cudaDriverEntryPointQueryResult qr;
        cudaGetDriverEntryPoint("cuTensorMapEncodeTiled", &fn, cudaEnableDefault, &qr);
        enc = (EncodeFn)fn;
        cudaFuncSetAttribute(fused_kernel, cudaFuncAttributeMaxDynamicSharedMemorySize, SM_TOTAL);
        cudaGetSymbolAddress((void**)&scratch, g_scratch);
        int dev = 0, nsm = 0;
        cudaGetDevice(&dev); cudaDeviceGetAttribute(&nsm, cudaDevAttrMultiProcessorCount, dev);
        by_sm = nsm == NCTA + NIDLE;
        roles.k16 = 0x10000;
        for (int t = 0; t < 66; t++) roles.pair[t] = t < 32 ? (t & 7) * 8 + (t >> 3) : (t < 60 ? (1 + (t - 32) % 7) * 8 + 4 + (t - 32) / 7 : (t < 62 ? t + 4 : t - 58));
    }
    CUtensorMap tx, tw, twt, two, td, tg, tu, to;
    encode(enc, &tx, x, 3, 640, 1024, 2, 2560, 1280, 64, 64, 2, CU_TENSOR_MAP_SWIZZLE_128B);
    encode(enc, &tw, wqkv, 3, 640, 640, 3, 3840, 1280, 64, 32, 3, CU_TENSOR_MAP_SWIZZLE_128B);
    encode(enc, &twt, wqkv, 3, 640, 640, 3, 3840, 1280, 16, 32, 3, CU_TENSOR_MAP_SWIZZLE_32B);
    encode(enc, &two, wo, 2, 640, 640, 1, 1280, 0, 64, 80, 1, CU_TENSOR_MAP_SWIZZLE_128B);
    encode(enc, &td, wd, 2, 640, 1728, 1, 1280, 0, 64, 32, 1, CU_TENSOR_MAP_SWIZZLE_128B);
    encode(enc, &to, d_out, 3, 640, 1024, 2, 2560, 1280, 80, 16, 1, CU_TENSOR_MAP_SWIZZLE_NONE);
    encode(enc, &tg, wg, 2, 1728, 640, 1, 3456, 0, 32, 80, 1, CU_TENSOR_MAP_SWIZZLE_64B);
    encode(enc, &tu, wu, 2, 1728, 640, 1, 3456, 0, 32, 80, 1, CU_TENSOR_MAP_SWIZZLE_64B);
    fused_kernel<<<NCTA + NIDLE, NTHREADS, SM_TOTAL>>>(scratch, x, wqkv, wo, wr, wd, (__nv_bfloat16*)d_out, by_sm, roles, tx, tw, twt, two, td, tg, tu, to);
}
```

```cpp
#include <cuda_runtime.h>
#include <cuda_bf16.h>
#include <cuda.h>
#include <stdint.h>

#define DEVI __device__ __forceinline__

namespace fk {

constexpr int DM = 640;
constexpr int NCTA = 128, NIDLE = 4, NTHREADS = 512;
constexpr int NMOE = 54;
constexpr int STAGE = 47104;
constexpr int OFF_B = 16384, B_HALF = 15360;
constexpr int SM_DW = 0;
constexpr int SM_WO = 33792;
constexpr int SM_G7 = SM_WO + 81920;
constexpr int SM_WT = SM_G7 + 5120;
constexpr int SM_EX = 3 * STAGE;
constexpr int SM_O0 = 3 * STAGE + OFF_B, SM_O1 = 4 * STAGE, SM_O2 = SM_DW;
constexpr int SM_MW = 4 * STAGE;
constexpr int SM_BX = SM_MW + 35840;
constexpr int SM_XSEL = SM_BX + 2560;
constexpr int SM_ST = SM_XSEL + 2592;
constexpr int SM_GT = SM_ST + 1152;
constexpr int SM_H = SM_GT + 320;
constexpr int SM_TOP = SM_XSEL + 1280;
constexpr int SM_BAR = SM_H + 128;
constexpr int SM_TL = SM_BAR + 368;
constexpr int SM_TOTAL = SM_TL;
static_assert(SM_TOTAL <= 232448 && SM_BAR % 8 == 0 && SM_XSEL % 16 == 0 && SM_ST % 16 == 0 && SM_GT % 16 == 0 && SM_BX % 1024 == 0 && SM_TOP % 16 == 0, "smem layout");
constexpr int BAR_FULL = 0, BAR_EMPTY = 4, BAR_WR = 8, BAR_Y = 9, BAR_GW = 10, BAR_DW = 11, BAR_PX = 12, BAR_RS = 13, BAR_SEL = 14, BAR_GI = 15, BAR_CX = 42, BAR_PG = 43, BAR_WT = 44,
              BAR_OF = 16  , BAR_OE = 21  , BAR_WO = 25, BAR_CS = 26, BAR_PA = 27  , BAR_AE = 32  , BAR_FA = 38  , NBAR = 45;
#define POLL_NS 100
#define PF1_NS 200
#define STAG 3
#define GP0 3
#define DP0 99
constexpr uint32_t EMPTY_WORD = 0xffffffffu;
struct Roles { unsigned k16, zero; unsigned short pair[NCTA / 2 + NIDLE / 2]; };
constexpr unsigned SPIN_MAX = 1u << 20;

struct Outbox {
    uint4 msg[192];
    uint4 gt[2][32];
};
struct Scratch {
    uint4 o[16][5][8][256];
    uint4 halo[NCTA][320];
    unsigned flag[16][8][8];
    Outbox box[NIDLE];
    uint4 cs[8][8][2][32];
    uint4 yp[8][56][40];
    uint2 rowinfo[16][2][64];
    unsigned rdone[NCTA][8];
    unsigned open[NIDLE][32];
    unsigned epoch[(NCTA + NIDLE) * 32];
};
__device__ Scratch g_scratch;
#define TL(i) do { } while (0)
#define GT(i) do { } while (0)

DEVI uint32_t smem_u32(const void* p) { return (uint32_t)__cvta_generic_to_shared(p); }
DEVI void mbar_init(uint32_t bar, uint32_t cnt) { asm volatile("mbarrier.init.shared::cta.b64 [%0], %1;" :: "r"(bar), "r"(cnt)); }
DEVI void mbar_expect_tx(uint32_t bar, uint32_t bytes) { asm volatile("mbarrier.arrive.expect_tx.shared::cta.b64 _, [%0], %1;" :: "r"(bar), "r"(bytes) : "memory"); }
DEVI void mbar_arrive(uint32_t bar) { asm volatile("mbarrier.arrive.shared::cta.b64 _, [%0];" :: "r"(bar) : "memory"); }
DEVI uint32_t clk32() { uint32_t t; asm volatile("mov.u32 %0, %%clock;" : "=r"(t) :: "memory"); return t; }
DEVI void sched_fence() { asm volatile("pmevent 0;" ::: "memory"); }
DEVI bool mbar_try(uint32_t bar, uint32_t parity) {
    uint32_t ok;
    asm volatile("{\n.reg .pred p;\nmbarrier.try_wait.parity.shared::cta.b64 p, [%1], %2, 0x989680;\nselp.u32 %0, 1, 0, p;\n}" : "=r"(ok) : "r"(bar), "r"(parity) : "memory");
    return ok != 0;
}
DEVI void mbar_wait(uint32_t bar, uint32_t parity) {
    while (!mbar_try(bar, parity)) { }
}
DEVI void mbar_spin(uint32_t bar, uint32_t parity) {
    uint32_t ok;
    do { asm volatile("{\n.reg .pred p;\nmbarrier.try_wait.parity.shared::cta.b64 p, [%1], %2;\nselp.u32 %0, 1, 0, p;\n}" : "=r"(ok) : "r"(bar), "r"(parity) : "memory"); } while (!ok);
}
DEVI bool elect_one() {
    uint32_t p;
    asm volatile("{\n.reg .pred P;\nelect.sync _|P, 0xffffffff;\nselp.u32 %0, 1, 0, P;\n}" : "=r"(p));
    return p != 0;
}
DEVI void tma3d(uint32_t dst, const CUtensorMap* tm, uint32_t bar, int c0, int c1, int c2) {
    asm volatile("cp.async.bulk.tensor.3d.shared::cluster.global.mbarrier::complete_tx::bytes [%0], [%1, {%3, %4, %5}], [%2];"
                 :: "r"(dst), "l"(tm), "r"(bar), "r"(c0), "r"(c1), "r"(c2) : "memory");
}
DEVI void tma3d_mc(uint32_t dst, const CUtensorMap* tm, uint32_t bar, int c0, int c1, int c2) {
    asm volatile("cp.async.bulk.tensor.3d.shared::cluster.global.mbarrier::complete_tx::bytes.multicast::cluster [%0], [%1, {%3, %4, %5}], [%2], %6;"
                 :: "r"(dst), "l"(tm), "r"(bar), "r"(c0), "r"(c1), "r"(c2), "h"((uint16_t)3) : "memory");
}
DEVI void tma2d(uint32_t dst, const CUtensorMap* tm, uint32_t bar, int c0, int c1) {
    asm volatile("cp.async.bulk.tensor.2d.shared::cluster.global.mbarrier::complete_tx::bytes [%0], [%1, {%3, %4}], [%2];"
                 :: "r"(dst), "l"(tm), "r"(bar), "r"(c0), "r"(c1) : "memory");
}
DEVI void tma2d_prefetch(const CUtensorMap* tm, int c0, int c1) {
    asm volatile("cp.async.bulk.prefetch.tensor.2d.L2.global [%0, {%1, %2}];" :: "l"(tm), "r"(c0), "r"(c1) : "memory");
}
DEVI void tma2d_mc(uint32_t dst, const CUtensorMap* tm, uint32_t bar, int c0, int c1) {
    asm volatile("cp.async.bulk.tensor.2d.shared::cluster.global.mbarrier::complete_tx::bytes.multicast::cluster [%0], [%1, {%3, %4}], [%2], %5;"
                 :: "r"(dst), "l"(tm), "r"(bar), "r"(c0), "r"(c1), "h"((uint16_t)3) : "memory");
}
DEVI void mbar_arrive_both(uint32_t bar) {
    asm volatile("{\n.reg .b32 ra;\nmapa.shared::cluster.u32 ra, %0, 0;\nmbarrier.arrive.shared::cluster.b64 _, [ra];\n"
                 "mapa.shared::cluster.u32 ra, %0, 1;\nmbarrier.arrive.shared::cluster.b64 _, [ra];\n}" :: "r"(bar) : "memory");
}
DEVI void mbar_arrive_at(uint32_t bar, uint32_t cta) {
    asm volatile("{\n.reg .b32 ra;\nmapa.shared::cluster.u32 ra, %0, %1;\nmbarrier.arrive.shared::cluster.b64 _, [ra];\n}" :: "r"(bar), "r"(cta) : "memory");
}
DEVI void st_halo(bool global, void* pg, uint32_t ps, uint32_t a, uint32_t b, uint32_t c, uint32_t d) {
    asm volatile("{\n.reg .pred p;\nsetp.ne.b32 p, %0, 0;\n@p st.relaxed.gpu.global.v4.u32 [%1], {%3,%4,%5,%6};\n@!p st.shared.v4.u32 [%2], {%3,%4,%5,%6};\n}"
                 :: "r"((uint32_t)global), "l"(pg), "r"(ps), "r"(a), "r"(b), "r"(c), "r"(d) : "memory");
}
DEVI uint4 ld_halo(bool global, const void* pg, uint32_t ps) {
    uint4 v;
    asm volatile("{\n.reg .pred p;\nsetp.ne.b32 p, %4, 0;\n@p ld.relaxed.gpu.global.v4.u32 {%0,%1,%2,%3}, [%5];\n@!p ld.shared.v4.u32 {%0,%1,%2,%3}, [%6];\n}"
                 : "=r"(v.x), "=r"(v.y), "=r"(v.z), "=r"(v.w) : "r"((uint32_t)global), "l"(pg), "r"(ps) : "memory");
    return v;
}
DEVI void bar_sync_id(int id, int n) { asm volatile("bar.sync %0, %1;" :: "r"(id), "r"(n) : "memory"); }
DEVI void st_async_peer(uint32_t addr, uint32_t bar, uint32_t peer, uint32_t v) {
    asm volatile("{\n.reg .b32 ra, rb;\nmapa.shared::cluster.u32 ra, %0, %2;\nmapa.shared::cluster.u32 rb, %1, %2;\n"
                 "st.async.weak.shared::cluster.mbarrier::complete_tx::bytes.b32 [ra], %3, [rb];\n}" :: "r"(addr), "r"(bar), "r"(peer), "r"(v) : "memory");
}
DEVI void st_async_v2(uint32_t addr, uint32_t bar, uint32_t cta, float a, float b) {
    asm volatile("{\n.reg .b32 ra, rb;\nmapa.shared::cluster.u32 ra, %0, %2;\nmapa.shared::cluster.u32 rb, %1, %2;\n"
                 "st.async.weak.shared::cluster.mbarrier::complete_tx::bytes.v2.f32 [ra], {%3,%4}, [rb];\n}" :: "r"(addr), "r"(bar), "r"(cta), "f"(a), "f"(b) : "memory");
}
DEVI void st_async_v4(uint32_t addr, uint32_t bar, uint32_t cta, float a, float b, float c, float d) {
    asm volatile("{\n.reg .b32 ra, rb;\nmapa.shared::cluster.u32 ra, %0, %2;\nmapa.shared::cluster.u32 rb, %1, %2;\n"
                 "st.async.weak.shared::cluster.mbarrier::complete_tx::bytes.v4.f32 [ra], {%3,%4,%5,%6}, [rb];\n}" :: "r"(addr), "r"(bar), "r"(cta), "f"(a), "f"(b), "f"(c), "f"(d) : "memory");
}
DEVI void bulk_load(uint32_t dst, const void* src, uint32_t bytes, uint32_t bar) {
    asm volatile("cp.async.bulk.shared::cluster.global.mbarrier::complete_tx::bytes [%0], [%1], %2, [%3];" :: "r"(dst), "l"(src), "r"(bytes), "r"(bar) : "memory");
}
DEVI void cluster_arrive() { asm volatile("barrier.cluster.arrive.relaxed.aligned;" ::: "memory"); }
DEVI void cluster_wait() { asm volatile("barrier.cluster.wait.aligned;" ::: "memory"); }
DEVI void wg_fence() { asm volatile("wgmma.fence.sync.aligned;" ::: "memory"); }
DEVI void wg_commit() { asm volatile("wgmma.commit_group.sync.aligned;" ::: "memory"); }
template <int N> DEVI void wg_wait() { asm volatile("wgmma.wait_group.sync.aligned %0;" :: "n"(N) : "memory"); }
template <int ID, int N> DEVI void bar_sync() { asm volatile("bar.sync %0, %1;" :: "n"(ID), "n"(N) : "memory"); }
DEVI void spin_guard(unsigned& n) { if (++n > SPIN_MAX) __trap(); }
DEVI uint4 ld_relaxed_v4(const void* p) {
    uint4 v;
    asm volatile("ld.relaxed.gpu.global.v4.u32 {%0,%1,%2,%3}, [%4];" : "=r"(v.x), "=r"(v.y), "=r"(v.z), "=r"(v.w) : "l"(p) : "memory");
    return v;
}
DEVI void st_relaxed_v4(void* p, const uint4& v) {
    asm volatile("st.relaxed.gpu.global.v4.u32 [%0], {%1,%2,%3,%4};" :: "l"(p), "r"(v.x), "r"(v.y), "r"(v.z), "r"(v.w) : "memory");
}
DEVI unsigned ld_relaxed_u32(const void* p) { unsigned v; asm volatile("ld.relaxed.gpu.global.u32 %0, [%1];" : "=r"(v) : "l"(p) : "memory"); return v; }
DEVI unsigned ld_acquire_u32(const void* p) { unsigned v; asm volatile("ld.acquire.gpu.global.u32 %0, [%1];" : "=r"(v) : "l"(p) : "memory"); return v; }
DEVI void st_relaxed_u32(void* p, unsigned v) { asm volatile("st.relaxed.gpu.global.u32 [%0], %1;" :: "l"(p), "r"(v) : "memory"); }
DEVI void st_relaxed_v2(void* p, unsigned a, unsigned b) { asm volatile("st.relaxed.gpu.global.v2.u32 [%0], {%1,%2};" :: "l"(p), "r"(a), "r"(b) : "memory"); }
DEVI uint4 ld_gen_v4(const void* p) {
    uint4 v;
    asm volatile("ld.relaxed.gpu.v4.u32 {%0,%1,%2,%3}, [%4];" : "=r"(v.x), "=r"(v.y), "=r"(v.z), "=r"(v.w) : "l"(p) : "memory");
    return v;
}
DEVI void st_gen_v4(void* p, const uint4& v) { asm volatile("st.relaxed.gpu.v4.u32 [%0], {%1,%2,%3,%4};" :: "l"(p), "r"(v.x), "r"(v.y), "r"(v.z), "r"(v.w) : "memory"); }
DEVI float sqrt_approx(float x) { float y; asm("sqrt.approx.ftz.f32 %0, %1;" : "=f"(y) : "f"(x)); return y; }
DEVI void red_add_u32(unsigned* p, unsigned v) { asm volatile("red.relaxed.gpu.global.add.u32 [%0], %1;" :: "l"(p), "r"(v) : "memory"); }
DEVI void red_add_v4(void* p, float a, float b, float c, float d) {
    asm volatile("red.relaxed.gpu.global.add.v4.f32 [%0], {%1,%2,%3,%4};" :: "l"(p), "f"(a), "f"(b), "f"(c), "f"(d) : "memory");
}
DEVI float4 ld_relaxed_f4(const void* p) {
    float4 v;
    asm volatile("ld.relaxed.gpu.global.v4.f32 {%0,%1,%2,%3}, [%4];" : "=f"(v.x), "=f"(v.y), "=f"(v.z), "=f"(v.w) : "l"(p) : "memory");
    return v;
}
DEVI void tma3d_store(const CUtensorMap* tm, uint32_t src, int c0, int c1, int c2) {
    asm volatile("cp.async.bulk.tensor.3d.global.shared::cta.bulk_group [%0, {%2, %3, %4}], [%1];\ncp.async.bulk.commit_group;\ncp.async.bulk.wait_group.read 0;"
                 :: "l"(tm), "r"(src), "r"(c0), "r"(c1), "r"(c2) : "memory");
}
DEVI uint32_t lds_u16(uint32_t a) { unsigned short v; asm volatile("ld.shared.u16 %0, [%1];" : "=h"(v) : "r"(a)); return v; }
DEVI void fence_gpu() { asm volatile("fence.acq_rel.gpu;" ::: "memory"); }
DEVI uint4 ldg_v4(const void* p) {
    uint4 v;
    asm volatile("ld.global.L1::no_allocate.v4.u32 {%0,%1,%2,%3}, [%4];" : "=r"(v.x), "=r"(v.y), "=r"(v.z), "=r"(v.w) : "l"(p) : "memory");
    return v;
}
DEVI uint4 lds_v4(uint32_t a) { uint4 v; asm volatile("ld.shared.v4.u32 {%0,%1,%2,%3}, [%4];" : "=r"(v.x), "=r"(v.y), "=r"(v.z), "=r"(v.w) : "r"(a)); return v; }
DEVI void sts_v4(uint32_t a, const uint4& v) { asm volatile("st.shared.v4.u32 [%0], {%1,%2,%3,%4};" :: "r"(a), "r"(v.x), "r"(v.y), "r"(v.z), "r"(v.w) : "memory"); }
DEVI void sts_f4(uint32_t a, float x, float y, float z, float w) { asm volatile("st.shared.v4.f32 [%0], {%1,%2,%3,%4};" :: "r"(a), "f"(x), "f"(y), "f"(z), "f"(w) : "memory"); }
DEVI float2 lds_f2(uint32_t a) { float2 v; asm volatile("ld.shared.v2.f32 {%0,%1}, [%2];" : "=f"(v.x), "=f"(v.y) : "r"(a)); return v; }
DEVI float4 lds_f4(uint32_t a) { float4 v; asm volatile("ld.shared.v4.f32 {%0,%1,%2,%3}, [%4];" : "=f"(v.x), "=f"(v.y), "=f"(v.z), "=f"(v.w) : "r"(a)); return v; }
DEVI void ldsm4(uint32_t addr, uint32_t& a, uint32_t& b, uint32_t& c, uint32_t& d) {
    asm volatile("ldmatrix.sync.aligned.m8n8.x4.shared.b16 {%0,%1,%2,%3}, [%4];" : "=r"(a), "=r"(b), "=r"(c), "=r"(d) : "r"(addr));
}
DEVI void ldsm4_if(bool on, uint32_t addr, uint32_t (&v)[4]) {
    asm volatile("{\n.reg .pred p;\nsetp.ne.b32 p, %5, 0;\n@p ldmatrix.sync.aligned.m8n8.x4.shared.b16 {%0,%1,%2,%3}, [%4];\n}"
                 : "+r"(v[0]), "+r"(v[1]), "+r"(v[2]), "+r"(v[3]) : "r"(addr), "r"((uint32_t)on));
}
DEVI void ldsm4t(uint32_t addr, uint32_t (&v)[4]) {
    asm volatile("ldmatrix.sync.aligned.m8n8.x4.trans.shared.b16 {%0,%1,%2,%3}, [%4];" : "=r"(v[0]), "=r"(v[1]), "=r"(v[2]), "=r"(v[3]) : "r"(addr));
}
DEVI void ldsm2(uint32_t addr, uint32_t& a, uint32_t& b) { asm volatile("ldmatrix.sync.aligned.m8n8.x2.shared.b16 {%0,%1}, [%2];" : "=r"(a), "=r"(b) : "r"(addr)); }
DEVI void cp_async16(uint32_t dst, const void* src) { asm volatile("cp.async.cg.shared.global [%0], [%1], 16;" :: "r"(dst), "l"(src) : "memory"); }
DEVI void prefetch_l2_bulk(const void* p, uint32_t bytes) { asm volatile("cp.async.bulk.prefetch.L2.global [%0], %1;" :: "l"(p), "r"(bytes) : "memory"); }
DEVI void sts_u16(uint32_t a, uint32_t v) { asm volatile("st.shared.u16 [%0], %1;" :: "r"(a), "h"((unsigned short)v) : "memory"); }
DEVI uint32_t hfma2(uint32_t a, uint32_t b, uint32_t c) { uint32_t d; asm("fma.rn.bf16x2 %0, %1, %2, %3;" : "=r"(d) : "r"(a), "r"(b), "r"(c)); return d; }
DEVI uint32_t imul(uint32_t a, uint32_t b) { uint32_t d; asm("mul.lo.u32 %0, %1, %2;" : "=r"(d) : "r"(a), "r"(b)); return d; }
DEVI float tanh_f(float x) { float t; asm("tanh.approx.f32 %0, %1;" : "=f"(t) : "f"(x)); return t; }
DEVI void stsm4(uint32_t addr, uint32_t a, uint32_t b, uint32_t c, uint32_t d) {
    asm volatile("stmatrix.sync.aligned.m8n8.x4.shared.b16 [%0], {%1,%2,%3,%4};" :: "r"(addr), "r"(a), "r"(b), "r"(c), "r"(d) : "memory");
}
DEVI uint32_t movm(uint32_t a) { uint32_t d; asm("movmatrix.sync.aligned.m8n8.trans.b16 %0, %1;" : "=r"(d) : "r"(a)); return d; }
DEVI void mma16(float (&c)[4], uint32_t a0, uint32_t a1, uint32_t a2, uint32_t a3, uint32_t b0, uint32_t b1) {
    asm("mma.sync.aligned.m16n8k16.row.col.f32.bf16.bf16.f32 {%0,%1,%2,%3}, {%4,%5,%6,%7}, {%8,%9}, {%0,%1,%2,%3};"
                 : "+f"(c[0]), "+f"(c[1]), "+f"(c[2]), "+f"(c[3]) : "r"(a0), "r"(a1), "r"(a2), "r"(a3), "r"(b0), "r"(b1));
}
DEVI void mma8(float (&c)[4], uint32_t a0, uint32_t a1, uint32_t b0) {
    asm("mma.sync.aligned.m16n8k8.row.col.f32.bf16.bf16.f32 {%0,%1,%2,%3}, {%4,%5}, {%6}, {%0,%1,%2,%3};"
                 : "+f"(c[0]), "+f"(c[1]), "+f"(c[2]), "+f"(c[3]) : "r"(a0), "r"(a1), "r"(b0));
}
DEVI uint32_t pack_bf16(float lo, float hi) { uint32_t d; asm("cvt.rn.bf16x2.f32 %0, %1, %2;" : "=r"(d) : "f"(hi), "f"(lo)); return d; }
DEVI float bf_lo(uint32_t v) { return __uint_as_float(v << 16); }
DEVI float bf_hi(uint32_t v) { return __uint_as_float(v & 0xffff0000u); }
DEVI float bfr(float x) { return __bfloat162float(__float2bfloat16_rn(x)); }
DEVI uint32_t tagf(float v, unsigned tag) { return (__float_as_uint(v) & ~15u) | (tag & 15); }
DEVI float ex2(float x) { float y; asm("ex2.approx.ftz.f32 %0, %1;" : "=f"(y) : "f"(x)); return y; }
DEVI float rcp(float x) { float y; asm("rcp.approx.ftz.f32 %0, %1;" : "=f"(y) : "f"(x)); return y; }
DEVI float sigmoid_f(float x) { return rcp(1.0f + ex2(x * -1.4426950408889634f)); }
DEVI float silu_f(float x) { const float h = 0.5f * x; float t; asm("tanh.approx.f32 %0, %1;" : "=f"(t) : "f"(h)); return fmaf(h, t, h); }
DEVI uint32_t hsub2(uint32_t a, uint32_t b) { uint32_t d; asm("sub.rn.bf16x2 %0, %1, %2;" : "=r"(d) : "r"(a), "r"(b)); return d; }
DEVI uint32_t hadd2(uint32_t a, uint32_t b) { uint32_t d; asm("add.rn.bf16x2 %0, %1, %2;" : "=r"(d) : "r"(a), "r"(b)); return d; }
DEVI uint32_t hmul2(uint32_t a, uint32_t b) { uint32_t d; asm("mul.rn.bf16x2 %0, %1, %2;" : "=r"(d) : "r"(a), "r"(b)); return d; }
DEVI uint32_t dup_hi(float x) { return __byte_perm(__float_as_uint(x), 0, 0x3232); }
DEVI void sts_u32(uint32_t a, uint32_t v) { asm volatile("st.shared.u32 [%0], %1;" :: "r"(a), "r"(v) : "memory"); }
DEVI void sts_f2(uint32_t a, float x, float y) { asm volatile("st.shared.v2.f32 [%0], {%1,%2};" :: "r"(a), "f"(x), "f"(y) : "memory"); }
DEVI uint2 lds_v2(uint32_t a) { uint2 v; asm volatile("ld.shared.v2.u32 {%0,%1}, [%2];" : "=r"(v.x), "=r"(v.y) : "r"(a)); return v; }
DEVI uint32_t lds_u32(uint32_t a) { uint32_t v; asm volatile("ld.shared.u32 %0, [%1];" : "=r"(v) : "r"(a)); return v; }
DEVI float lds_f32(uint32_t a) { float v; asm volatile("ld.shared.f32 %0, [%1];" : "=f"(v) : "r"(a)); return v; }
DEVI float shfl_x(float v, int o) { return __shfl_xor_sync(0xffffffffu, v, o); }

DEVI void wgmma_rs_n192(float (&d)[120], uint32_t a0, uint32_t a1, uint32_t a2, uint32_t a3, uint32_t blo, uint32_t scale_d) {
    asm volatile("{\n.reg .b64 db;\n.reg .pred p;\n"
        "setp.ne.b32 p, %101, 0;\n"
        "mov.b64 db, {%100, 0x40000040};\n"
        "wgmma.mma_async.sync.aligned.m64n192k16.f32.bf16.bf16 "
        "{%0, %1, %2, %3, %4, %5, %6, %7, %8, %9, %10, %11, %12, %13, %14, %15, %16, %17, %18, %19, %20, %21, %22, %23, %24, %25, %26, %27, %28, %29, %30, %31, %32, %33, %34, %35, %36, %37, %38, %39, %40, %41, %42, %43, %44, %45, %46, %47, %48, %49, %50, %51, %52, %53, %54, %55, %56, %57, %58, %59, %60, %61, %62, %63, %64, %65, %66, %67, %68, %69, %70, %71, %72, %73, %74, %75, %76, %77, %78, %79, %80, %81, %82, %83, %84, %85, %86, %87, %88, %89, %90, %91, %92, %93, %94, %95}, "
        "{%96, %97, %98, %99}, db, p, 1, 1, 1;\n}\n"
        : "+f"(d[0]), "+f"(d[1]), "+f"(d[2]), "+f"(d[3]), "+f"(d[4]), "+f"(d[5]), "+f"(d[6]), "+f"(d[7]), "+f"(d[8]), "+f"(d[9]), "+f"(d[10]), "+f"(d[11]), "+f"(d[12]), "+f"(d[13]), "+f"(d[14]), "+f"(d[15]), "+f"(d[16]), "+f"(d[17]), "+f"(d[18]), "+f"(d[19]), "+f"(d[20]), "+f"(d[21]), "+f"(d[22]), "+f"(d[23]), "+f"(d[24]), "+f"(d[25]), "+f"(d[26]), "+f"(d[27]), "+f"(d[28]), "+f"(d[29]), "+f"(d[30]), "+f"(d[31]), "+f"(d[32]), "+f"(d[33]), "+f"(d[34]), "+f"(d[35]), "+f"(d[36]), "+f"(d[37]), "+f"(d[38]), "+f"(d[39]), "+f"(d[40]), "+f"(d[41]), "+f"(d[42]), "+f"(d[43]), "+f"(d[44]), "+f"(d[45]), "+f"(d[46]), "+f"(d[47]), "+f"(d[48]), "+f"(d[49]), "+f"(d[50]), "+f"(d[51]), "+f"(d[52]), "+f"(d[53]), "+f"(d[54]), "+f"(d[55]), "+f"(d[56]), "+f"(d[57]), "+f"(d[58]), "+f"(d[59]), "+f"(d[60]), "+f"(d[61]), "+f"(d[62]), "+f"(d[63]), "+f"(d[64]), "+f"(d[65]), "+f"(d[66]), "+f"(d[67]), "+f"(d[68]), "+f"(d[69]), "+f"(d[70]), "+f"(d[71]), "+f"(d[72]), "+f"(d[73]), "+f"(d[74]), "+f"(d[75]), "+f"(d[76]), "+f"(d[77]), "+f"(d[78]), "+f"(d[79]), "+f"(d[80]), "+f"(d[81]), "+f"(d[82]), "+f"(d[83]), "+f"(d[84]), "+f"(d[85]), "+f"(d[86]), "+f"(d[87]), "+f"(d[88]), "+f"(d[89]), "+f"(d[90]), "+f"(d[91]), "+f"(d[92]), "+f"(d[93]), "+f"(d[94]), "+f"(d[95])
        : "r"(a0), "r"(a1), "r"(a2), "r"(a3), "r"(blo), "r"(scale_d));
}
DEVI void wgmma_rs_n48(float (&d)[120], uint32_t a0, uint32_t a1, uint32_t a2, uint32_t a3, uint32_t blo, uint32_t scale_d) {
    asm volatile("{\n.reg .b64 db;\n.reg .pred p;\n"
        "setp.ne.b32 p, %29, 0;\n"
        "mov.b64 db, {%28, 0xc0000010};\n"
        "wgmma.mma_async.sync.aligned.m64n48k16.f32.bf16.bf16 "
        "{%0, %1, %2, %3, %4, %5, %6, %7, %8, %9, %10, %11, %12, %13, %14, %15, %16, %17, %18, %19, %20, %21, %22, %23}, "
        "{%24, %25, %26, %27}, db, p, 1, 1, 1;\n}\n"
        : "+f"(d[96]), "+f"(d[97]), "+f"(d[98]), "+f"(d[99]), "+f"(d[100]), "+f"(d[101]), "+f"(d[102]), "+f"(d[103]), "+f"(d[104]), "+f"(d[105]), "+f"(d[106]), "+f"(d[107]), "+f"(d[108]), "+f"(d[109]), "+f"(d[110]), "+f"(d[111]), "+f"(d[112]), "+f"(d[113]), "+f"(d[114]), "+f"(d[115]), "+f"(d[116]), "+f"(d[117]), "+f"(d[118]), "+f"(d[119])
        : "r"(a0), "r"(a1), "r"(a2), "r"(a3), "r"(blo), "r"(scale_d));
}
DEVI void wgmma_rs_n192x(float (&d)[120], uint32_t a0, uint32_t a1, uint32_t a2, uint32_t a3, uint32_t blo) {
    asm volatile("{\n.reg .b64 db;\n.reg .pred p;\n"
        "mov.b64 db, {%100, 0x40000000};\n"
        "wgmma.mma_async.sync.aligned.m64n192k16.f32.bf16.bf16 "
        "{%0, %1, %2, %3, %4, %5, %6, %7, %8, %9, %10, %11, %12, %13, %14, %15, %16, %17, %18, %19, %20, %21, %22, %23, %24, %25, %26, %27, %28, %29, %30, %31, %32, %33, %34, %35, %36, %37, %38, %39, %40, %41, %42, %43, %44, %45, %46, %47, %48, %49, %50, %51, %52, %53, %54, %55, %56, %57, %58, %59, %60, %61, %62, %63, %64, %65, %66, %67, %68, %69, %70, %71, %72, %73, %74, %75, %76, %77, %78, %79, %80, %81, %82, %83, %84, %85, %86, %87, %88, %89, %90, %91, %92, %93, %94, %95}, "
        "{%96, %97, %98, %99}, db, 1, 1, 1, 1;\n}\n"
        : "+f"(d[0]), "+f"(d[1]), "+f"(d[2]), "+f"(d[3]), "+f"(d[4]), "+f"(d[5]), "+f"(d[6]), "+f"(d[7]), "+f"(d[8]), "+f"(d[9]), "+f"(d[10]), "+f"(d[11]), "+f"(d[12]), "+f"(d[13]), "+f"(d[14]), "+f"(d[15]), "+f"(d[16]), "+f"(d[17]), "+f"(d[18]), "+f"(d[19]), "+f"(d[20]), "+f"(d[21]), "+f"(d[22]), "+f"(d[23]), "+f"(d[24]), "+f"(d[25]), "+f"(d[26]), "+f"(d[27]), "+f"(d[28]), "+f"(d[29]), "+f"(d[30]), "+f"(d[31]), "+f"(d[32]), "+f"(d[33]), "+f"(d[34]), "+f"(d[35]), "+f"(d[36]), "+f"(d[37]), "+f"(d[38]), "+f"(d[39]), "+f"(d[40]), "+f"(d[41]), "+f"(d[42]), "+f"(d[43]), "+f"(d[44]), "+f"(d[45]), "+f"(d[46]), "+f"(d[47]), "+f"(d[48]), "+f"(d[49]), "+f"(d[50]), "+f"(d[51]), "+f"(d[52]), "+f"(d[53]), "+f"(d[54]), "+f"(d[55]), "+f"(d[56]), "+f"(d[57]), "+f"(d[58]), "+f"(d[59]), "+f"(d[60]), "+f"(d[61]), "+f"(d[62]), "+f"(d[63]), "+f"(d[64]), "+f"(d[65]), "+f"(d[66]), "+f"(d[67]), "+f"(d[68]), "+f"(d[69]), "+f"(d[70]), "+f"(d[71]), "+f"(d[72]), "+f"(d[73]), "+f"(d[74]), "+f"(d[75]), "+f"(d[76]), "+f"(d[77]), "+f"(d[78]), "+f"(d[79]), "+f"(d[80]), "+f"(d[81]), "+f"(d[82]), "+f"(d[83]), "+f"(d[84]), "+f"(d[85]), "+f"(d[86]), "+f"(d[87]), "+f"(d[88]), "+f"(d[89]), "+f"(d[90]), "+f"(d[91]), "+f"(d[92]), "+f"(d[93]), "+f"(d[94]), "+f"(d[95])
        : "r"(a0), "r"(a1), "r"(a2), "r"(a3), "r"(blo));
}
DEVI void wgmma_rs_n48x(float (&d)[120], uint32_t a0, uint32_t a1, uint32_t a2, uint32_t a3, uint32_t blo) {
    asm volatile("{\n.reg .b64 db;\n.reg .pred p;\n"
        "mov.b64 db, {%28, 0xc0000000};\n"
        "wgmma.mma_async.sync.aligned.m64n48k16.f32.bf16.bf16 "
        "{%0, %1, %2, %3, %4, %5, %6, %7, %8, %9, %10, %11, %12, %13, %14, %15, %16, %17, %18, %19, %20, %21, %22, %23}, "
        "{%24, %25, %26, %27}, db, 1, 1, 1, 1;\n}\n"
        : "+f"(d[96]), "+f"(d[97]), "+f"(d[98]), "+f"(d[99]), "+f"(d[100]), "+f"(d[101]), "+f"(d[102]), "+f"(d[103]), "+f"(d[104]), "+f"(d[105]), "+f"(d[106]), "+f"(d[107]), "+f"(d[108]), "+f"(d[109]), "+f"(d[110]), "+f"(d[111]), "+f"(d[112]), "+f"(d[113]), "+f"(d[114]), "+f"(d[115]), "+f"(d[116]), "+f"(d[117]), "+f"(d[118]), "+f"(d[119])
        : "r"(a0), "r"(a1), "r"(a2), "r"(a3), "r"(blo));
}
DEVI void wgmma_rs_n80(float (&d)[40], uint32_t a0, uint32_t a1, uint32_t a2, uint32_t a3, uint32_t blo, uint32_t scale_d) {
    asm volatile("{\n.reg .b64 db;\n.reg .pred p;\n"
        "setp.ne.b32 p, %45, 0;\n"
        "mov.b64 db, {%44, 0x40000040};\n"
        "wgmma.mma_async.sync.aligned.m64n80k16.f32.bf16.bf16 "
        "{%0, %1, %2, %3, %4, %5, %6, %7, %8, %9, %10, %11, %12, %13, %14, %15, %16, %17, %18, %19, %20, %21, %22, %23, %24, %25, %26, %27, %28, %29, %30, %31, %32, %33, %34, %35, %36, %37, %38, %39}, "
        "{%40, %41, %42, %43}, db, p, 1, 1, 1;\n}\n"
        : "+f"(d[0]), "+f"(d[1]), "+f"(d[2]), "+f"(d[3]), "+f"(d[4]), "+f"(d[5]), "+f"(d[6]), "+f"(d[7]), "+f"(d[8]), "+f"(d[9]), "+f"(d[10]), "+f"(d[11]), "+f"(d[12]), "+f"(d[13]), "+f"(d[14]), "+f"(d[15]), "+f"(d[16]), "+f"(d[17]), "+f"(d[18]), "+f"(d[19]), "+f"(d[20]), "+f"(d[21]), "+f"(d[22]), "+f"(d[23]), "+f"(d[24]), "+f"(d[25]), "+f"(d[26]), "+f"(d[27]), "+f"(d[28]), "+f"(d[29]), "+f"(d[30]), "+f"(d[31]), "+f"(d[32]), "+f"(d[33]), "+f"(d[34]), "+f"(d[35]), "+f"(d[36]), "+f"(d[37]), "+f"(d[38]), "+f"(d[39])
        : "r"(a0), "r"(a1), "r"(a2), "r"(a3), "r"(blo), "r"(scale_d));
}
DEVI void wgmma_ss_n80(float (&d)[40], uint32_t alo, uint32_t blo) {
    asm volatile("{\n.reg .b64 da, db;\n"
        "mov.b64 da, {%40, 0x10};\n"
        "mov.b64 db, {%41, 0x40000040};\n"
        "wgmma.mma_async.sync.aligned.m64n80k16.f32.bf16.bf16 "
        "{%0, %1, %2, %3, %4, %5, %6, %7, %8, %9, %10, %11, %12, %13, %14, %15, %16, %17, %18, %19, %20, %21, %22, %23, %24, %25, %26, %27, %28, %29, %30, %31, %32, %33, %34, %35, %36, %37, %38, %39}, "
        "da, db, 1, 1, 1, 0, 1;\n}\n"
        : "+f"(d[0]), "+f"(d[1]), "+f"(d[2]), "+f"(d[3]), "+f"(d[4]), "+f"(d[5]), "+f"(d[6]), "+f"(d[7]), "+f"(d[8]), "+f"(d[9]), "+f"(d[10]), "+f"(d[11]), "+f"(d[12]), "+f"(d[13]), "+f"(d[14]), "+f"(d[15]), "+f"(d[16]), "+f"(d[17]), "+f"(d[18]), "+f"(d[19]), "+f"(d[20]), "+f"(d[21]), "+f"(d[22]), "+f"(d[23]), "+f"(d[24]), "+f"(d[25]), "+f"(d[26]), "+f"(d[27]), "+f"(d[28]), "+f"(d[29]), "+f"(d[30]), "+f"(d[31]), "+f"(d[32]), "+f"(d[33]), "+f"(d[34]), "+f"(d[35]), "+f"(d[36]), "+f"(d[37]), "+f"(d[38]), "+f"(d[39])
        : "r"(alo), "r"(blo));
}

DEVI unsigned redux_max(unsigned v) { return __reduce_max_sync(0xffffffffu, v); }

DEVI void service_cta(Scratch* __restrict__ sc, const __nv_bfloat16* __restrict__ x, const __nv_bfloat16* __restrict__ wr, uint32_t sb, int h, int tid) {
    const int warp = tid >> 5, lane = tid & 31;
    Outbox* const box = &sc->box[h];
    const unsigned tag = ld_relaxed_u32(&sc->epoch[(NCTA + h) * 32]) + 1;
    if (tid < 256) st_relaxed_v4(&box->msg[0] + tid, make_uint4(EMPTY_WORD, EMPTY_WORD, EMPTY_WORD, EMPTY_WORD));
    __syncthreads();
    unsigned spins = 0;
    if (warp == 0) {
        fence_gpu();
        if (lane < 2) st_relaxed_v4(&sc->open[h][lane * 4], make_uint4(tag, tag, tag, tag));
    }
    if (warp >= 8) {
        const int t = tid - 256;
        float wsum = 0.f;
        __nanosleep(1000);
#pragma unroll
        for (int j = 0; j < 10; j++) { const uint32_t v = reinterpret_cast<const uint32_t*>(wr)[lane + 32 * j]; wsum += bf_lo(v) + bf_hi(v); }
#pragma unroll
        for (int o = 1; o < 32; o <<= 1) wsum += shfl_x(wsum, o);
        uint4 q[4];
        const uint4* src = reinterpret_cast<const uint4*>(&sc->rowinfo[0][0][0]) + t;
#pragma unroll
        for (int j = 0; j < 4; j++) q[j].y = q[j].w = tag - 1;
        while (true) {
            unsigned bad = 0;
#pragma unroll
            for (int j = 0; j < 4; j++) if (((q[j].y ^ tag) | (q[j].w ^ tag)) & 15) q[j] = ld_relaxed_v4(src + 256 * j);
            __syncwarp();
#pragma unroll
            for (int j = 0; j < 4; j++) bad |= (q[j].y ^ tag) | (q[j].w ^ tag);
            if (__all_sync(0xffffffffu, (bad & 15) == 0)) break;
            if (spins == 0) while (!__any_sync(0xffffffffu, ((ld_relaxed_v4(src).y ^ tag) & 15) == 0)) { __nanosleep(100); spin_guard(spins); }
            spin_guard(spins);
        }
        if (t == 0) TL(2);
        unsigned a = 0, b = 0;
#pragma unroll
        for (int j = 0; j < 8; j++) {
            const uint32_t info = (j & 1) ? q[j >> 1].z : q[j >> 1].x;
            const uint32_t u = pack_bf16(fmaf(-bf_lo(info), wsum, __uint_as_float((j & 1) ? q[j >> 1].w : q[j >> 1].y)) * rcp(bf_hi(info)), 0.f);
            const int row = ((j >> 1) * 4 + (t >> 6)) * 128 + 4 * (t & 31) + 2 * (j & 1) + ((t >> 5) & 1);
            const unsigned key = (((u & 0x8000u) ? (u ^ 0xffffu) : (u | 0x8000u)) << 16) | ((2047 - row) << 5);
            b = max(b, min(a, key)); a = max(a, key);
        }
        unsigned k1 = redux_max(a), k2 = redux_max(a == k1 ? b : a);
        if (lane == 0) sts_f2(sb + 8192 + (warp - 8) * 8, __uint_as_float(k1), __uint_as_float(k2));
        bar_sync<2, 256>();
        a = lds_u32(sb + 8192 + (lane & 15) * 4);
        k1 = redux_max(a); k2 = redux_max(a == k1 ? 0u : a);
        if (t < 160) {
            const int tk = t >= 80, sel = 2047 - (((tk ? k2 : k1) >> 5) & 2047);
            const uint4 xq = ldg_v4(reinterpret_cast<const uint4*>(x + sel * DM) + t - tk * 80);
            const unsigned info = ld_relaxed_u32(&sc->rowinfo[sel >> 7][sel & 1][(sel & 127) >> 1]);
            const uint32_t mm = __byte_perm(info, 0, 0x1010);
            const float rs = rcp(bf_hi(info));
            uint32_t o[4];
#pragma unroll
            for (int e = 0; e < 4; e++) { const uint32_t d = hsub2((&xq.x)[e], mm); o[e] = pack_bf16(bf_lo(d) * rs, bf_hi(d) * rs); }
            st_relaxed_v4(&box->msg[t + tk], make_uint4(o[0], o[1], o[2], o[3]));
            sts_v4(sb + SM_XSEL + (t + tk) * 16, make_uint4(o[0], o[1], o[2], o[3]));
        } else if (t == 160) {
            const uint4 top = make_uint4(2047 - ((k1 >> 5) & 2047), 2047 - ((k2 >> 5) & 2047), k1, k2);
            st_relaxed_v4(&box->msg[80], top); sts_v4(sb + SM_TOP, top);
        }
        if (t == 0) TL(3);
    }
    __syncthreads();
    const uint4* src = &sc->yp[2 * h + (warp >> 3)][warp & 7][0];
    uint4 v[7]; unsigned u[7];
#pragma unroll
    for (int j = 0; j < 7; j++) v[j].x = u[j] = (j == 6 && (warp & 7) >= 6) ? tag : tag - 1;
    spins = 0;
    while (NMOE) {
        unsigned bad = 0;
#pragma unroll
        for (int j = 0; j < 7; j++)
            if (((v[j].x ^ tag) | (u[j] ^ tag)) & 15) { v[j] = ld_relaxed_v4(src + j * 320 + lane); u[j] = ld_relaxed_u32(reinterpret_cast<const unsigned*>(src + j * 320 + 32) + lane); }
        __syncwarp();
#pragma unroll
        for (int j = 0; j < 7; j++) bad |= (v[j].x ^ tag) | (u[j] ^ tag);
        if (__all_sync(0xffffffffu, (bad & 15) == 0)) break;
        if (spins == 0) while (!__any_sync(0xffffffffu, ((ld_relaxed_u32(src + min(lane & 7, 5) * 320 + 32) ^ tag) & 15) == 0)) { __nanosleep(100); spin_guard(spins); }
        spin_guard(spins);
    }
    if (tid == 0) TL(4);
    float y[5] = {0.f, 0.f, 0.f, 0.f, 0.f};
#pragma unroll
    for (int j = 0; j < 7; j++) {
        if (NMOE && (j < 6 || (warp & 7) < 6)) {
            y[0] += __uint_as_float(v[j].x); y[1] += __uint_as_float(v[j].y); y[2] += __uint_as_float(v[j].z); y[3] += __uint_as_float(v[j].w); y[4] += __uint_as_float(u[j]);
        }
    }
#pragma unroll
    for (int e = 0; e < 5; e++) sts_u32(sb + (warp * 160 + e * 32 + lane) * 4, __float_as_uint(y[e]));
    __syncthreads();
    if (warp < 10) {
        const int gi = warp >= 5, e = warp - 5 * gi, tk = lane & 1, col = e * 16 + (lane >> 2) + 4 * (lane & 2);
        float sum = 0.f;
#pragma unroll
        for (int j = 0; j < 8; j++) sum += lds_f32(sb + ((gi * 8 + j) * 160 + e * 32 + lane) * 4);
        const uint32_t ks = lds_u32(sb + SM_TOP + 8 + tk * 4) >> 16;
        const float sg = bfr(sigmoid_f(__uint_as_float(((ks & 0x8000u) ? (ks & 0x7fffu) : (ks ^ 0xffffu)) << 16)));
        sts_u16(sb + 16384 + gi * 512 + tk * 160 + col * 2,
                pack_bf16(silu_f(bfr(bf_lo(lds_u16(sb + SM_XSEL + tk * 1296 + ((2 * h + gi) * 80 + col) * 2)) + bfr(bfr(sum) * sg))), 0.f));
        bar_sync<1, 320>();
        if (warp < 2 && lane < 20) st_relaxed_v4(&box->gt[warp][lane], lds_v4(sb + 16384 + tid * 16));
    }
    if (tid == 0) { st_relaxed_u32(&sc->epoch[(NCTA + h) * 32], tag); TL(5); }
}

template <int ODD, int HALF> DEVI void pack_kv(const float (&acc)[120], uint32_t (&K)[10][2], uint32_t (&V)[10][2]) {
#pragma unroll
    for (int b = 0; b < 10; b++) {
        const int pb = ODD ? (b + 8) % 10 : b, jk = pb < 8 ? 8 + pb : 18 + pb, jv = pb < 8 ? 16 + pb : 20 + pb;
        V[b][HALF] = movm(pack_bf16(acc[4 * jv + 2 * HALF], acc[4 * jv + 2 * HALF + 1]));
        K[b][HALF] = pack_bf16(acc[4 * jk + 2 * HALF], acc[4 * jk + 2 * HALF + 1]);
    }
}
template <int ODD> DEVI void pack_q(const float (&acc)[120], uint32_t (&Q)[10][2]) {
#pragma unroll
    for (int b = 0; b < 10; b++) {
        const int pb = ODD ? (b + 8) % 10 : b, jq = pb < 8 ? pb : 16 + pb;
        Q[b][0] = pack_bf16(acc[4 * jq], acc[4 * jq + 1]); Q[b][1] = pack_bf16(acc[4 * jq + 2], acc[4 * jq + 3]);
    }
}

#define KROT 5
#define WOP 8
#define SIDE_N -1
#define PIPE_POLL 0
#define NSIDE 4
#define WO_S 6
#define TAIL_NS 50
#define WO_GATE 2
#define MSG_NS 800
#define T2_NS 0
#define JL 6
#define G7T 10
#define PRE_D 1
#define POLL2 0
#define POLL2_GAP 60
#define G1S 0
#define XJ 2
#define FXN 4
#define SWAP 0
#define MSGW 0
#define TAILM 0
#define WTT 10
#define MSG_POLL 100
#define DPN 4
#define GI_T 0
#define SPLIT 3
#define RS_PACE(t) (t)
#define ATS(i)
#define G1_DONE() do { if ((tid & 127) == 32) mbar_arrive(bars + BAR_GI * 8); } while (0)
#define SRC(i) ((i) == 0 ? g : ((i) - 1 < g ? (i) - 1 : (i)))

__global__ void __cluster_dims__(2, 1, 1) __launch_bounds__(NTHREADS, 1) fused_kernel(
    Scratch* __restrict__ sc,
    const __nv_bfloat16* __restrict__ x, const __nv_bfloat16* __restrict__ wqkv, const __nv_bfloat16* __restrict__ wo, const __nv_bfloat16* __restrict__ wr,
    const __nv_bfloat16* __restrict__ wd, __nv_bfloat16* __restrict__ out, const int by_sm, const __grid_constant__ Roles roles,
    const __grid_constant__ CUtensorMap tm_x, const __grid_constant__ CUtensorMap tm_w, const __grid_constant__ CUtensorMap tm_wt,
    const __grid_constant__ CUtensorMap tm_wo, const __grid_constant__ CUtensorMap tm_wn, const __grid_constant__ CUtensorMap tm_d,
    const __grid_constant__ CUtensorMap tm_g, const __grid_constant__ CUtensorMap tm_u, const __grid_constant__ CUtensorMap tm_o)
{
    extern __shared__ __align__(1024) unsigned char smem[];
    const uint32_t bid = blockIdx.x, tid = threadIdx.x;
    uint32_t sb, smid;
    asm volatile("mov.u32 %0, %1;" : "=r"(sb) : "r"(smem_u32(smem)));
    asm volatile("mov.u32 %0, %%smid;" : "=r"(smid));
    const unsigned cta = roles.pair[(by_sm ? smid : bid) >> 1] * 2 + (bid & 1);
    const int warp = __shfl_sync(0xffffffffu, tid >> 5, 0), lane = tid & 31;
    const uint32_t bars = sb + SM_BAR;
#define BAR_COUNT(s) ((s >> 2) == 1 ? 4 : (s >= BAR_AE ? (s >= BAR_FA ? 1 : (s == BAR_AE + 5 ? 2 : 4)) : (s >= BAR_PA ? 8 : (s == BAR_CS || s == BAR_OE + 1 ? 4 : (s >= BAR_OE + 2 || s == BAR_GI ? 2 : 1)))))
#define INIT_BARS(a, b) do { if (elect_one()) { _Pragma("unroll") for (int s = a; s < b; s++) if (s != BAR_FA || (a) == BAR_FA) mbar_init(bars + s * 8, BAR_COUNT(s)); \
        asm volatile("fence.mbarrier_init.release.cluster;" ::: "memory"); } __syncwarp(); } while (0)
    if (warp >= 8) {
        if (warp == 8) INIT_BARS(BAR_FA, BAR_FA + 1);
        else if (warp == 9) INIT_BARS(0, 23);
        else if (warp == 10) INIT_BARS(23, NBAR);
    }
    cluster_arrive();
    if (warp < 2) {
        const uint32_t i = tid - 32;
        if (tid < 30 && bid < NCTA) asm volatile("prefetch.global.L2 [%0];" :: "l"(reinterpret_cast<const char*>(wqkv) + (bid * 15 + tid + (tid >= 15 ? KROT * 1920 - 15 : 0)) * 128) : "memory");
        if (i < 16) asm volatile("prefetch.global.L2 [%0];" :: "l"(bid < NCTA ? reinterpret_cast<const char*>(x) + (bid * 16 + i) * 1280 + (bid & 16) * (KROT * 8)
                                                                             : reinterpret_cast<const char*>(wr) + min(i, 9u) * 128) : "memory");
    }
    if (cta >= NCTA) { cluster_wait(); service_cta(sc, x, wr, sb, cta - NCTA, tid); return; }
    const int rank = cta & 1, g = (cta >> 1) & 7, G = cta >> 4, m = 2 * G + rank, odd = g & 1;
    const int k0 = (G & 1) * KROT * 64;
    const int cm = g * 80 + odd * 16, ct = g * 80 + 64 - odd * 64;

#define NP0 2
#define TILE_X(kt, kk) tma3d(sb + (-(kt) & 3) * STAGE, &tm_x, bars + (BAR_FA + ((kt) & 3)) * 8, kk, m * 64, 0)
#define TILE_W(kt, kk) do { const uint32_t fb_ = bars + (BAR_FULL + ((kt) & 3)) * 8, st_ = sb + (-(kt) & 3) * STAGE + OFF_B; \
        tma3d_mc(st_ + rank * B_HALF, &tm_w, fb_, cm, (kk) + rank * 32, 0); \
        tma3d(st_ + 12288, &tm_wt, fb_, ct, kk, 0); tma3d(st_ + B_HALF + 12288, &tm_wt, fb_, ct, (kk) + 32, 0); } while (0)
    if (warp == 8) {
        if (elect_one()) { mbar_expect_tx(bars + BAR_FA * 8, OFF_B); TILE_X(0, k0); }
        cluster_wait();
        if (elect_one()) {
            mbar_expect_tx(bars + BAR_FULL * 8, 2 * B_HALF);
            TILE_W(0, k0);
            mbar_expect_tx(bars + BAR_WR * 8, 1280); bulk_load(sb + SM_XSEL, wr, 1280, bars + BAR_WR * 8);
            TL(16);
#pragma unroll
            for (int kt = 1; kt < NP0; kt++) {
                mbar_expect_tx(bars + (BAR_FA + kt) * 8, OFF_B); mbar_expect_tx(bars + (BAR_FULL + kt) * 8, 2 * B_HALF);
                TILE_X(kt, k0 + kt * 64); TILE_W(kt, k0 + kt * 64);
                if (kt == 1) TL(29);
            }
        }
        __syncwarp();
    }
    if (warp >= 8) {
        asm volatile("setmaxnreg.dec.sync.aligned.u32 72;");
        const int mi = g < 6 ? G * 6 + g : 46 + G;
        const bool moe = g < 6 || (g == 6 && G >= 2);
        if (warp == 8) {
            const CUtensorMap* tm_gu = rank ? &tm_u : &tm_g;
            if (elect_one()) { mbar_expect_tx(bars + BAR_WO * 8, 81920); mbar_expect_tx(bars + BAR_GW * 8, 40960); mbar_expect_tx(bars + BAR_DW * 8, 20480); }
#pragma unroll 1
            for (int kt = NP0; kt < 13; kt++) {
                if (kt >= 4) { if (kt < 4 + JL) mbar_wait(bars + (BAR_AE + kt - 4) * 8, 0); mbar_wait(bars + (BAR_EMPTY + (kt & 3)) * 8, ((kt >> 2) - 1) & 1); }
                if (elect_one()) {
                    if (kt < 10) {
                        const int kk = kt * 64 + (kt < 5 ? k0 : -k0);
                        mbar_expect_tx(bars + (BAR_FA + (kt & 3)) * 8, OFF_B); mbar_expect_tx(bars + (BAR_FULL + (kt & 3)) * 8, 2 * B_HALF);
                        TILE_X(kt, kk); TILE_W(kt, kk);
                        if (kt == WOP) prefetch_l2_bulk(reinterpret_cast<const char*>(wo) + cta * 6400, 6400);
                    }
                    if (moe) {
                        if ((unsigned)(kt - GP0) < 7u) tma2d(sb + SM_MW + (kt - GP0) * 5120, tm_gu, bars + BAR_GW * 8, mi * 32, (kt - GP0) * 80);
                        if (kt == G7T) tma2d(sb + SM_G7, tm_gu, bars + BAR_GW * 8, mi * 32, 560);
                        if ((unsigned)(kt - DP0) < (unsigned)DPN) prefetch_l2_bulk(wd + (mi * 32 + rank * 16 + (kt - DP0) * (16 / DPN)) * DM, 20480 / DPN);
                        if (kt == 12) {
#pragma unroll
                            for (int i = 0; i < 5; i++) tma2d(sb + SM_DW + i * 4096, &tm_d, bars + BAR_DW * 8, (rank * 5 + i) * 64, mi * 32);
                        }
                    }
                    if (kt == 3) TL(17);
                }
                __syncwarp();
                if (kt >= 10) {
                    if (kt == 11 && (WO_GATE & 2)) mbar_wait(bars + BAR_RS * 8, 0);
                    if (kt == 12 && (WO_GATE & 4)) mbar_wait(bars + BAR_SEL * 8, 0);
                    if (elect_one()) {
                        if (TAILM && kt == WTT) { mbar_expect_tx(bars + BAR_WT * 8, 20480); tma3d(sb + SM_WT, &tm_wn, bars + BAR_WT * 8, ct, 0, 0); }
#pragma unroll
                        for (int i0 = (kt == 10 ? 0 : (kt == 11 ? 2 : WO_S)); i0 < (kt == 10 ? 2 : (kt == 11 ? WO_S : 8)); i0 += 2) {
                            const int i = i0 + rank;
                            tma2d_mc(sb + SM_WO + (7 - i) * 10240, &tm_wo, bars + BAR_WO * 8, cm, SRC(i) * 80);
                        }
                    }
                    __syncwarp();
                }
            }
            const uint4* os = &sc->o[m][0][0][0];
            const unsigned* fl = &sc->flag[m][(lane & 7) == g ? g ^ 1 : lane & 7][0];
            const uint4* os2 = os + (g + 1) * 256;
            const uint32_t n1 = g * 4096, n2 = 28672 - n1;
            asm volatile("" : "+l"(fl));
            if (elect_one()) {
#pragma unroll
                for (int t = 0; t < 5; t++) mbar_expect_tx(bars + (BAR_OF + t) * 8, 28672);
            }
            mbar_wait(bars + BAR_GI * 8, 0);
            if (lane == 0) mbar_arrive_at(bars + BAR_PG * 8, rank ^ 1);
            mbar_wait(bars + BAR_PG * 8, 0);
            mbar_wait(bars + BAR_PA * 8, 0);
            unsigned lvl = 0, spins = 0;
#pragma unroll
            for (int t = 0; t < 5; t++) {
                while (__any_sync(0xffffffffu, lvl <= t)) {
                    lvl = ld_relaxed_u32(fl);
                    spin_guard(spins);
                }
                if (t) mbar_wait(bars + (BAR_OE + t - 1) * 8, 0);
                if (elect_one()) {
                    const uint32_t dst = sb + (t == 2 ? SM_O2 : ((t == 0 || t == 3) ? SM_O0 : SM_O1)), fb = bars + (BAR_OF + t) * 8;
                    if (g > 0) bulk_load(dst, os + t * 2048, n1, fb);
                    if (g < 7) bulk_load(dst + n1, os2 + t * 2048, n2, fb);
                    TL(48 + t);
                }
                __syncwarp();
            }
        } else {
            const int ta = tid - 288, wa = (SWAP && warp >= 12 ? warp ^ 2 : warp) - 9, c = lane & 3, r = lane >> 2;
            const unsigned tag = ld_relaxed_u32(&sc->epoch[cta * 32]) + 1;
            const Outbox* const box = &sc->box[g >> 1];
#define FETCH_MSG() do { \
                while (ld_relaxed_u32(&box->msg[80]) == EMPTY_WORD) { __nanosleep(MSG_POLL); spin_guard(spins); } \
                if (lane == 0) TL(61); \
                uint4 q[6]; \
                while (true) { \
                    _Pragma("unroll") for (int j = 0; j < 6; j++) q[j] = ld_relaxed_v4(&box->msg[min(lane + 32 * j, 160)]); \
                    __syncwarp(); \
                    if (__all_sync(0xffffffffu, max(max(max(q[0].x, q[1].x), max(q[2].x, q[3].x)), max(q[4].x, q[5].x)) != EMPTY_WORD)) break; \
                    spin_guard(spins); \
                } \
                _Pragma("unroll") for (int j = 0; j < 6; j++) sts_v4(sb + SM_XSEL + min(lane + 32 * j, 160) * 16, q[j]); \
                __syncwarp(); \
                if (lane == 0) { mbar_arrive(bars + BAR_SEL * 8); TL(23); } } while (0)
            unsigned spins = 0;
            if (wa == 0) {
                uint4 *ro = &sc->o[m][0][g][lane], *rh = &sc->halo[m * 8 + g][lane];
                if (lane < 2) st_relaxed_v4(&sc->rdone[m * 8 + g][lane * 4], make_uint4(0, 0, 0, 0));
                cluster_wait();
                if (lane == 0) mbar_expect_tx(bars + BAR_PX * 8, 2560);
#pragma unroll 1
                for (int t = 0; t < 5; t++, ro += 2048, rh += 64) {
                    mbar_wait(bars + (BAR_AE + RS_PACE(t)) * 8, 0);
                    const uint4 e = make_uint4(EMPTY_WORD, EMPTY_WORD, EMPTY_WORD, EMPTY_WORD);
#pragma unroll
                    for (int i = 0; i < 8; i++) st_relaxed_v4(ro + 32 * i, e);
                    st_relaxed_v4(rh, e); st_relaxed_v4(rh + 32, e);
                }
                if (lane < 2) st_relaxed_v4(&sc->flag[m][g][lane * 4], make_uint4(0, 0, 0, 0));
                fence_gpu();
                __syncwarp();
                if (lane == 0) { st_relaxed_u32(&sc->rdone[m * 8 + g][0], tag); TL(20); }
                const unsigned* rd = lane == 9 ? &sc->open[g >> 1][0] : &sc->rdone[m * 8 + (lane == 8 && m > 0 ? g - 8 : lane & 7)][0];
                while (!__all_sync(0xffffffffu, ld_relaxed_u32(rd) == tag)) { __nanosleep(POLL_NS); spin_guard(spins); }
                if (lane == 0) { mbar_arrive(bars + BAR_RS * 8); TL(21); }
                if (MSGW == 0) FETCH_MSG();
                unsigned* fo = &sc->flag[m][g][0];
                asm volatile("" : "+l"(fo));
                mbar_wait(bars + BAR_GI * 8, 0);
#pragma unroll 1
                for (int t = 0; t < 5; t++) { mbar_spin(bars + (BAR_PA + t) * 8, 0); if (lane == 0) st_relaxed_u32(fo, t + 1); }
                return;
            } else {
                const bool cw = wa < 3, aside = wa >= 5;
                const int l = min(lane, 29), part = l < 24 ? l >> 3 : (l - 24) >> 1;
                const int pp = warp & 1, ri = lane >> 3;
                float s[8];
#pragma unroll
                for (int e = 0; e < 8; e++) s[e] = 0.f;
                const uint32_t k16 = roles.k16, khi = 0x3f800000u;
#define U_LO(v) __uint_as_float(imul(v, k16))
#define U_HI(v) __uint_as_float(hfma2(v, khi, 0u))
#define GAPS 1
#define GAP(...) do { if (GAPS) { asm volatile("pmevent 0;" : __VA_ARGS__ :: "memory"); } } while (0)
#define ROW_SUMS(v0, v1, v2) do { _Pragma("unroll") for (int e = 0; e < 4; e++) { \
                    const float wl = U_LO((&v2.x)[e]), wh = U_HI((&v2.x)[e]), a = U_LO((&v0.x)[e]), b = U_HI((&v0.x)[e]); \
                    s[0] += a; s[1] = fmaf(a, a, s[1]); s[2] = fmaf(a, wl, s[2]); s[0] += b; s[1] = fmaf(b, b, s[1]); s[2] = fmaf(b, wh, s[2]); \
                    GAP("+f"(s[0]), "+f"(s[1]), "+f"(s[2]), "+r"((&v1.x)[e])); \
                    const float a2 = U_LO((&v1.x)[e]), b2 = U_HI((&v1.x)[e]); \
                    s[4] += a2; s[5] = fmaf(a2, a2, s[5]); s[6] = fmaf(a2, wl, s[6]); s[4] += b2; s[5] = fmaf(b2, b2, s[5]); s[6] = fmaf(b2, wh, s[6]); \
                    GAP("+f"(s[4]), "+f"(s[5]), "+f"(s[6]), "+r"((&v0.x)[(e + 1) & 3]), "+r"((&v2.x)[(e + 1) & 3])); } } while (0)
                if (aside) {
                    const __nv_bfloat16* p0 = x + (m * 128 + g * 16 + 2 * ri + pp) * DM + 64 * JL - k0 + (lane & 7) * 8;
                    const uint32_t wa2 = sb + SM_XSEL + (lane & 7) * 16 + 128 * JL - 2 * k0;
                    cluster_wait();
                    mbar_wait(bars + BAR_WR * 8, 0);
                    if (SIDE_N >= 0) mbar_wait(bars + (BAR_AE + SIDE_N) * 8, 0);
                    uint4 q[10 - JL][2];
#pragma unroll
                    for (int j = 0; j < 10 - JL; j++) { q[j][0] = ldg_v4(p0 + j * 64); q[j][1] = ldg_v4(p0 + 8 * DM + j * 64); }
                    uint4 wn = lds_v4(wa2);
                    __syncwarp();
#pragma unroll
                    for (int j = 0; j < 10 - JL; j++) { uint4 wv = wn; if (j < 9 - JL) wn = lds_v4(wa2 + (j + 1) * 128); ROW_SUMS(q[j][0], q[j][1], wv); }
                    if (wa == 5 && lane == 0) TL(62);
                } else {
                    uint32_t ad[4];
#pragma unroll
                    for (int i = 0; i < 4; i++) {
                        const int row = 4 * ((G & 6) + pp) + i;
                        ad[i] = cw ? OFF_B + rank * B_HALF + (l < 24 ? part * 4096 + row * 128 + (((l ^ row) & 7) << 4) : 12288 + part * 1024 + row * 32 + (((l ^ pp) & 1) << 4))
                                   : (i < 2 ? pp * 8192 + (8 * g + ri + 4 * i) * 128 + (((lane ^ (ri + 4 * i)) & 7) << 4) : SM_XSEL + (lane & 7) * 16 + 2 * k0);
                        ad[i] = __shfl_sync(0xffffffffu, sb + ad[i], lane);
                    }
                    if (wa == 1) st_relaxed_v4(&sc->cs[g][G][rank][lane], make_uint4(tag - 1, 0, 0, 0));
                    cluster_wait();
                    if (ta == 32) mbar_expect_tx(bars + BAR_CX * 8, 2048);
                    mbar_wait(bars + BAR_WR * 8, 0);
#pragma unroll 1
                    for (int kt = 0; kt < (cw ? 5 : JL); kt++) {
                        const uint32_t so = (-kt & 3) * STAGE;
                        mbar_wait(bars + ((cw ? BAR_FULL : BAR_FA) + (kt & 3)) * 8, kt >> 2);
                        uint4 v0 = lds_v4(ad[0] + so), v1 = lds_v4(ad[1] + so), v2 = lds_v4(ad[2] + (cw ? so : kt * 128 - (kt == 5 ? 4 * k0 : 0)));
                        if (cw) {
                            const uint4 v3 = lds_v4(ad[3] + so);
#pragma unroll
                            for (int e = 0; e < 4; e++) {
                                s[2 * e] += U_LO((&v0.x)[e]); s[2 * e + 1] += U_HI((&v0.x)[e]); s[2 * e] += U_LO((&v1.x)[e]); s[2 * e + 1] += U_HI((&v1.x)[e]);
                                s[2 * e] += U_LO((&v2.x)[e]); s[2 * e + 1] += U_HI((&v2.x)[e]); s[2 * e] += U_LO((&v3.x)[e]); s[2 * e + 1] += U_HI((&v3.x)[e]);
                                GAP("+f"(s[2 * e]), "+f"(s[2 * e + 1]));
                            }
                        } else ROW_SUMS(v0, v1, v2);
                        __syncwarp();
                        if (lane == 0) mbar_arrive(bars + (BAR_AE + kt) * 8);
                    }
                }
                if (cw) {
                    const uint32_t cx = sb + SM_BX + (rank * 2 + pp) * 512 + lane * 16;
                    st_async_v4(cx, bars + BAR_CX * 8, 0, s[0], s[1], s[2], s[3]); st_async_v4(cx, bars + BAR_CX * 8, 1, s[4], s[5], s[6], s[7]);
                    if (wa == 1) {
                        mbar_wait(bars + BAR_CX * 8, 0);
                        const uint32_t a = sb + SM_BX + lane * 16;
                        const float4 a0 = lds_f4(a), a1 = lds_f4(a + 512), a2 = lds_f4(a + 1024), a3 = lds_f4(a + 1536);
                        st_relaxed_v4(&sc->cs[g][G][rank][lane], make_uint4(tagf((a0.x + a1.x) + (a2.x + a3.x), tag), __float_as_uint((a0.y + a1.y) + (a2.y + a3.y)),
                                                                            __float_as_uint((a0.z + a1.z) + (a2.z + a3.z)), __float_as_uint((a0.w + a1.w) + (a2.w + a3.w))));
                        if (lane == 0) TL(18);
#pragma unroll 1
                        for (int i = lane; i < 140; i += 32) sts_v4(sb + SM_BX + i * 16, make_uint4(0, 0, 0, 0));
                    }
                    bar_sync<7, 64>();
                    uint4 v[8];
#pragma unroll
                    for (int j = 0; j < 8; j++) v[j].x = tag - 1;
                    while (true) {
                        unsigned bad = 0;
#pragma unroll
                        for (int j = 0; j < 8; j++) if ((v[j].x ^ tag) & 15) v[j] = ld_relaxed_v4(&sc->cs[g][j][pp][l]);
                        __syncwarp();
#pragma unroll
                        for (int j = 0; j < 8; j++) bad |= v[j].x ^ tag;
                        if (__all_sync(0xffffffffu, (bad & 15) == 0)) break;
                        spin_guard(spins);
                    }
#pragma unroll
                    for (int e = 0; e < 4; e++) {
                        s[e] = 0.f;
#pragma unroll
                        for (int j = 0; j < 8; j++) s[e] += __uint_as_float((&v[j].x)[e]);
                    }
#pragma unroll
                    for (int j = 0; j < 3; j++) {
                        const int row = 3 * part + j;
                        const uint32_t o0 = pack_bf16(s[0], s[1]), o1 = pack_bf16(s[2], s[3]);
                        s[0] -= bf_lo(o0); s[1] -= bf_hi(o0); s[2] -= bf_lo(o1); s[3] -= bf_hi(o1);
                        sts_f2(sb + SM_BX + pp * 8 + (l < 24 ? row * 128 + (((l ^ row) & 7) << 4) : 1792 + row * 32 + (((l ^ (row >> 2)) & 1) << 4)), __uint_as_float(o0), __uint_as_float(o1));
                    }
                    asm volatile("fence.proxy.async.shared::cta;" ::: "memory");
                    __syncwarp();
                    if (lane == 0) { mbar_arrive(bars + BAR_CS * 8); TL(25); }
                } else {
#pragma unroll
                    for (int e = 0; e < 3; e++) s[e] = ((lane & 4) ? s[4 + e] : s[e]) + shfl_x((lane & 4) ? s[e] : s[4 + e], 4);
#pragma unroll
                    for (int o = 1; o < 4; o <<= 1) {
#pragma unroll
                        for (int e = 0; e < 3; e++) s[e] += shfl_x(s[e], o);
                    }
                    const uint32_t sa = sb + SM_GT + pp * 128 + r * 16;
                    if (aside) {
                        sts_f4(sa, s[0], s[1], s[2], 0.f); asm volatile("bar.arrive 6, 128;" ::: "memory");
                    }
                    else {
                        bar_sync<6, 128>();
                        const float4 o = lds_f4(sa);
                        const int row = 8 * g + ri + (lane & 4);
                        const float mean = (s[0] + o.x) * (1.0f / DM);
                        const float sd = sqrt_approx(bfr(bfr(fmaxf(fmaf(-mean, mean, (s[1] + o.y) * (1.0f / DM)), 0.f)) + 1e-5f));
                        if (c == 0) st_relaxed_v2(&sc->rowinfo[m][pp][row], pack_bf16(mean, sd), tagf(s[2] + o.z, tag));
                        if (wa == 3 && lane == 0) TL(22);
                    }
                    if (!aside) {
                        const uint4* r0 = reinterpret_cast<const uint4*>(&sc->rowinfo[m][pp][0]);
                        uint4 a, b;
                        while (true) {
                            __nanosleep(POLL_NS);
                            a = ld_relaxed_v4(r0 + lane); b = ld_relaxed_v4(r0 + (m > 0 ? 28 - 64 : 0) + c);
                            if (__all_sync(0xffffffffu, (((a.y ^ tag) | (a.w ^ tag) | (b.y ^ tag) | (b.w ^ tag)) & 15) == 0)) break;
                            spin_guard(spins);
                        }
                        sts_f4(sb + SM_ST + (pp * 72 + 8 + 2 * lane) * 8, bf_lo(a.x), rcp(bf_hi(a.x)), bf_lo(a.z), rcp(bf_hi(a.z)));
                        if (lane < 4) sts_f4(sb + SM_ST + (pp * 72 + 2 * lane) * 8, bf_lo(b.x), rcp(bf_hi(b.x)), bf_lo(b.z), rcp(bf_hi(b.z)));
                        __syncwarp();
                        if (lane == 0) { mbar_arrive(bars + BAR_CS * 8); if (pp == 0) TL(24); }
                    }
                }
            }
            if (wa == 6) {
                if (MSGW >= 6) while (ld_relaxed_u32(&sc->open[g >> 1][0]) != tag) spin_guard(spins);
                const int r = lane >> 1;
                mbar_wait(bars + (BAR_AE + JL - 1) * 8, 0); mbar_wait(bars + (BAR_FA + 2) * 8, 1); mbar_wait(bars + (BAR_EMPTY + 2) * 8, 1);
#pragma unroll 1
                for (int i = 0; i < 8; i++) {
                    const __nv_bfloat16* src = wo + (i * 80 + r) * DM + ct + (lane & 1) * 8;
                    const uint32_t dst = sb + SM_WT + (i & 1) * 10240 + r * 128 + ((((i & 6) + (lane & 1)) ^ (r & 7)) << 4);
#pragma unroll
                    for (int t = 0; t < 5; t++) cp_async16(dst + t * 2048, src + t * 16 * DM);
                    __nanosleep(TAIL_NS);
                }
                if (MSGW == 6) FETCH_MSG();
                asm volatile("cp.async.wait_all;" ::: "memory");
                asm volatile("fence.proxy.async.shared::cta;" ::: "memory");
                __syncwarp();
                if (lane == 0) { mbar_arrive(bars + BAR_WO * 8); TL(19); }
                return;
            }
            if (moe) {
                const int krow = (lane >> 4) * 8 + (lane & 7), ch = (lane >> 3) & 1;
                const uint32_t wp = sb + SM_MW + (wa - 1) * 1024 + krow * 64 + ((ch ^ (krow >> 1)) & 3) * 16;
                const uint32_t xa = sb + SM_XSEL + (lane & 1) * 1296 + ch * 16 + (wa - 1) * 32 + (lane >> 4) * 160;
                uint32_t a[10][4];
                mbar_wait(bars + BAR_GW * 8, 0);
#pragma unroll
                for (int i = 0; i < 10; i++)
                    ldsm4t(((wp + (i >> 1) * 5120) ^ ((i & 1) * 32)) + (i >= PRE_D ? a[i - PRE_D][0] & roles.zero : 0u), a[i]);
                float d[2][4];
#pragma unroll
                for (int e = 0; e < 8; e++) d[e >> 2][e & 3] = 0.f;
                mbar_wait(bars + BAR_SEL * 8, 0);
                mbar_wait(bars + BAR_GI * 8, 0);
                if (ta == 32) TL(26);
#pragma unroll
                for (int i = 0; i < 8; i += 2) {
                    uint32_t b[4];
                    ldsm4(xa + i * 160, b[0], b[1], b[2], b[3]);
#pragma unroll
                    for (int e = 0; e < 4; e++) {
                        uint32_t (&f)[4] = a[(2 * i + e) % 10];
                        mma16(d[e & 1], f[0], f[1], f[2], f[3], b[e & 2], b[(e & 2) + 1]);
                        if (2 * i + e < 6) ldsm4t((wp + (i + (e >> 1) == 2 ? SM_G7 - SM_MW : (i + (e >> 1) + 5) * 5120)) ^ ((e & 1) * 32), f);
                    }
                }
                {
                    const float u0 = (c & 2) ? ((c & 1) ? d[1][2] : d[1][0]) : ((c & 1) ? d[0][2] : d[0][0]);
                    const float u1 = (c & 2) ? ((c & 1) ? d[1][3] : d[1][1]) : ((c & 1) ? d[0][3] : d[0][1]);
                    const uint32_t dst = sb + SM_BX + (rank * 5 + wa - 1) * 256 + (c * 8 + r) * 8;
                    mbar_wait(bars + BAR_PG * 8, 0);
                    st_async_v2(dst, bars + BAR_PX * 8, 0, u0, u1); st_async_v2(dst, bars + BAR_PX * 8, 1, u0, u1);
                }
                if (wa >= 2) {
                    mbar_wait(bars + BAR_DW * 8, 0);
#pragma unroll
                    for (int b = 0; b < 5; b++) {
                        const int nb = (wa - 2) * 5 + b;
                        const uint32_t dp = sb + SM_DW + (nb >> 2) * 4096 + krow * 128 + ((((nb & 3) * 2 + ch) ^ (krow & 7)) << 4);
                        ldsm4t(dp, a[2 * b]); ldsm4t(dp + 2048, a[2 * b + 1]);
                    }
                } else {
                    mbar_wait(bars + BAR_PX * 8, 0);
                    if (lane == 0) { mbar_arrive(bars + BAR_OE * 8); TL(27); }
                    float2 gs = make_float2(0.f, 0.f), us = gs;
#pragma unroll
                    for (int e = 0; e < 5; e++) {
                        const float2 u = lds_f2(sb + SM_BX + e * 256 + lane * 8), v = lds_f2(sb + SM_BX + 1280 + e * 256 + lane * 8);
                        gs.x += u.x; gs.y += u.y; us.x += v.x; us.y += v.y;
                    }
                    const uint32_t g2 = pack_bf16(gs.x, gs.y);
                    const uint32_t h2 = hmul2(pack_bf16(bf_lo(g2) * sigmoid_f(bf_lo(g2)), bf_hi(g2) * sigmoid_f(bf_hi(g2))), pack_bf16(us.x, us.y));
                    sts_u16(sb + SM_H + lane * 2, h2); sts_u16(sb + SM_H + 64 + lane * 2, h2 >> 16);
                }
                bar_sync<3, 160>();
                if (wa >= 2) {
                    uint32_t hb[4];
                    ldsm4(sb + SM_H + (lane & 1) * 64 + (lane >> 3) * 16, hb[0], hb[1], hb[2], hb[3]);
                    float yv[5];
#pragma unroll
                    for (int b = 0; b < 5; b++) {
                        float o[4] = {0.f, 0.f, 0.f, 0.f};
                        mma16(o, a[2 * b][0], a[2 * b][1], a[2 * b][2], a[2 * b][3], hb[0], hb[1]);
                        mma16(o, a[2 * b + 1][0], a[2 * b + 1][1], a[2 * b + 1][2], a[2 * b + 1][3], hb[2], hb[3]);
                        yv[b] = (c & 2) ? ((c & 1) ? o[3] : o[2]) : ((c & 1) ? o[1] : o[0]);
                    }
                    uint4* const dst = &sc->yp[rank * 4 + wa - 2][mi][0];
                    st_relaxed_v4(dst + lane, make_uint4(tagf(yv[0], tag), __float_as_uint(yv[1]), __float_as_uint(yv[2]), __float_as_uint(yv[3])));
                    st_relaxed_u32(reinterpret_cast<unsigned*>(dst + 32) + lane, tagf(yv[4], tag));
                    if (lane == 0) mbar_arrive(bars + (BAR_OE + 1) * 8);
                    if (wa == 3 && lane == 0) TL(28);
                }
            } else if (lane == 0) mbar_arrive(bars + (BAR_OE + (wa > 1)) * 8);
            if (wa == 1) {
                mbar_wait(bars + BAR_SEL * 8, 0);
                const uint2 sel = lds_v2(sb + SM_TOP);
                if ((sel.x >> 7) == m || (sel.y >> 7) == m) {
                    uint4 v;
                    do { __nanosleep(POLL_NS); v = ld_relaxed_v4(&box->gt[g & 1][min(lane, 19)]); spin_guard(spins); } while (__any_sync(0xffffffffu, v.x == EMPTY_WORD));
                    sts_v4(sb + SM_GT + min(lane, 19) * 16, v);
                    __syncwarp();
                    if (lane == 0) TL(30);
                }
                if (lane == 0) { mbar_arrive(bars + BAR_Y * 8); st_relaxed_u32(&sc->epoch[cta * 32], tag); }
            }
        }
    } else {
        asm volatile("setmaxnreg.inc.sync.aligned.u32 184;");
        const int p = warp >> 2, w = warp & 3, c = lane & 3, r = lane >> 2;
        const uint32_t stb = sb + SM_ST + (p * 72 + w * 16) * 8;
        float acc[120];
#pragma unroll
        for (int i = 0; i < 120; i++) asm volatile("" : "=f"(acc[i]));
        uint32_t xs[5][4];
#pragma unroll
        for (int i = 0; i < 20; i++) asm volatile("" : "=r"(xs[i >> 2][i & 3]));
#define EXT_STEP() do {        \
            mbar_wait(bars + BAR_CS * 8, 0); \
            const uint32_t msk = c == 0 ? 0xffffffffu : (c == 1 ? 0x0000ffffu : 0u); \
            const uint32_t e0 = dup_hi(-lds_f32(stb + (8 + r) * 8)) & msk, e1 = dup_hi(-lds_f32(stb + (16 + r) * 8)) & msk; \
            wg_fence(); \
            wgmma_rs_n48x(acc, e0, e1, 0u, 0u, (((sb + SM_BX + 1792) & 0x3ffffu) >> 4) | ((96u >> 4) << 16)); \
            wgmma_rs_n192x(acc, e0, e1, 0u, 0u, (((sb + SM_BX) & 0x3ffffu) >> 4) | ((384u >> 4) << 16)); \
            wg_commit(); } while (0)
#define EXT_J 4
        cluster_wait();
        {
            const int lr = w * 16 + (lane & 15);
            uint32_t st = __shfl_sync(0xffffffffu, sb + p * 8192 + lr * 128 + (((lr & 7) ^ (lane >> 4)) << 4), lane);
            const bool lead = __shfl_sync(0xffffffffu, tid & 127, lane) == 0;
            uint32_t blo = (((sb + OFF_B) & 0x3ffffu) >> 4) | ((4096u >> 4) << 16);
            const uint32_t tdiff = (12288u >> 4) + ((1024u >> 4) << 16) - ((4096u >> 4) << 16);
            uint32_t xo[5]; unsigned long long xm = 0;
#pragma unroll
            for (int t = 0; t < 5; t++) {
                const int ks = 5 * g + (t < 4 ? t + odd : 4 - 4 * odd), kq = (ks >> 2) - (k0 >> 6);
                xo[t] = __shfl_sync(0xffffffffu, (ks & 3) << 5, lane);
                xm |= 1ull << (5 * (kq < 0 ? kq + 10 : kq) + t);
            }
#define PD 1
            asm volatile("" : "+l"(xm));
            sched_fence();
            uint32_t af[4][4];
            mbar_wait(bars + BAR_FA * 8, 0);
            ldsm4(st, af[0][0], af[0][1], af[0][2], af[0][3]);
            if (PD == 2) ldsm4(st ^ 32, af[1][0], af[1][1], af[1][2], af[1][3]);
#pragma unroll
            for (int kt = 0; kt < 10; kt++) {
#pragma unroll
                for (int j = 0; j < 4; j++) {
                    uint32_t (&nx)[4] = af[(j + PD) & 3];
                    if (j == 0) {
                        mbar_wait(bars + (BAR_FULL + (kt & 3)) * 8, (kt >> 2) & 1);
                    }
                    if (j == 4 - PD && kt < 9) {
                        st += (kt & 3) == 0 ? 3 * STAGE : -STAGE;
                        mbar_wait(bars + (BAR_FA + ((kt + 1) & 3)) * 8, ((kt + 1) >> 2) & 1);
                    }
                    if (G1S && j == (40 - G1S) % 4 && kt == (40 - G1S) / 4 && p == 1) bar_sync<8, 256>();
                    ldsm4(st ^ (((j + PD) & 3) << 5), nx[0], nx[1], nx[2], nx[3]);
                    wg_fence();
                    const uint32_t sd = j ? 1u : (uint32_t)kt;
                    wgmma_rs_n48(acc, af[j][0], af[j][1], af[j][2], af[j][3], blo + tdiff + (j >> 1) * (B_HALF >> 4) + (j & 1) * 32, sd);
                    wgmma_rs_n192(acc, af[j][0], af[j][1], af[j][2], af[j][3], blo + (j >> 1) * (B_HALF >> 4) + (j & 1) * 128, sd);
                    wg_commit();
#define WD 2
                    wg_wait<WD>();
                    if (j == WD - 1 && kt > 0 && lead) mbar_arrive_both(bars + (BAR_EMPTY + ((kt - 1) & 3)) * 8);
                    if (j == EXT_J && kt == 9) EXT_STEP();
                    if (j == XJ) {
                        if (xm & 31) {
#pragma unroll
                            for (int t = 0; t < 5; t++) ldsm4_if((xm >> t) & 1, st ^ xo[t], xs[t]);
                        }
                        xm >>= 5;
                    }
                }
                blo += (kt & 3) == 0 ? 3 * (STAGE >> 4) : -(STAGE >> 4);
            }
        }
        if (G1S && p == 0) asm volatile("bar.arrive 8, 256;" ::: "memory");
        if (EXT_J > 3) EXT_STEP();
        if (tid == 0) TL(10);
        const float2 st0 = lds_f2(stb + (8 + r) * 8), st1 = lds_f2(stb + (16 + r) * 8);
        const float rs0 = st0.y, rs1 = st1.y;
        const uint4 sP = lds_v4(stb + (2 * c) * 8), sB = lds_v4(stb + (8 + 2 * c) * 8), sC = lds_v4(stb + (16 + 2 * c) * 8);
        const bool up0 = 2 * c > r, up1 = 2 * c + 1 > r;
        float k00 = __uint_as_float(up0 ? sP.y : sB.y), k01 = __uint_as_float(up1 ? sP.w : sB.w);
        float k10 = __uint_as_float(up0 ? sB.y : sC.y), k11 = __uint_as_float(up1 ? sB.w : sC.w);
        const float sc2 = 0.22360679774997896f * 1.4426950408889634f;
        const uint32_t exs = __shfl_sync(0xffffffffu, sb + SM_EX + p * 8192 + w * 2560 + lane * 16, lane), exr = exs - (w ? 2560 : 0);
        uint4* hg = &sc->halo[m * 8 + g - (w ? 0 : 8)][p * 160 + lane];
        asm volatile("" : "+l"(hg));
        mbar_wait(bars + BAR_RS * 8, 0);
        if (p == 0) bar_sync<1, 128>(); else bar_sync<2, 128>();
        sched_fence();
        wg_wait<0>();
        if ((tid & 127) == 0) TL(2 + p);
        if (tid == 64) GT(59);
        uint32_t Q[10][2], K[10][2], V[10][2], Kp[10], Vp[10];
        uint4 rcv[5];
#define BX(h) (5 * ((h) >> 1) + 3 * ((h) & 1))
#define BZ(h) (5 * ((h) >> 1) + 2)
        float fa[4], fb[4], l[4][2];
        uint32_t qz[4][2], eh[4], ph[4];
        const bool first = (m == 0 && w == 0), far = (m > 0 && w == 0);
#define AV 4
#define MSK(a, b) hmul2(a, b)
        const uint32_t mup = (up0 ? 0x00003f80u : 0u) | (up1 ? 0x3f800000u : 0u), mdn = mup ^ 0x3f803f80u;
        const uint32_t qlo = c < 2;
#define SEND() do { \
            st_halo(w == 3, hg, exs, K[0][1], K[1][1], K[3][1], K[4][1]); st_halo(w == 3, hg + 32, exs + 512, K[5][1], K[6][1], K[8][1], K[9][1]); \
            st_halo(w == 3, hg + 64, exs + 1024, K[2][1], K[7][1], V[0][1], V[1][1]); st_halo(w == 3, hg + 96, exs + 1536, V[2][1], V[3][1], V[4][1], V[5][1]); \
            st_halo(w == 3, hg + 128, exs + 2048, V[6][1], V[7][1], V[8][1], V[9][1]); G1_DONE(); } while (0)
#define RECV() do { bar_sync_id(1 + p, 128); \
            if (AV & 2) { _Pragma("unroll") for (int i = 0; i < 5; i++) rcv[i] = ld_halo(far, hg + i * 32, exr + i * 512); } \
            else if (far) { _Pragma("unroll") for (int i = 0; i < 5; i++) rcv[i] = ld_relaxed_v4(hg + i * 32); } \
            else { _Pragma("unroll") for (int i = 0; i < 5; i++) rcv[i] = lds_v4(exr + i * 512); } } while (0)
#define OWN_KEYS(ODD) do { \
            asm volatile("" : "+f"(k00), "+f"(k01), "+f"(k10), "+f"(k11) :: "memory"); \
            const float f00 = rs0 * k00 * sc2, f01 = rs0 * k01 * sc2, f10 = rs1 * k10 * sc2, f11 = rs1 * k11 * sc2; \
            fa[0] = up0 ? f00 : 0.f; fa[1] = up1 ? f01 : 0.f; fa[2] = up0 ? f10 : 0.f; fa[3] = up1 ? f11 : 0.f; \
            fb[0] = f00 - fa[0]; fb[1] = f01 - fa[1]; fb[2] = f10 - fa[2]; fb[3] = f11 - fa[3]; \
            const float b00 = (first && up0) ? -1e30f : 0.f, b01 = (first && up1) ? -1e30f : 0.f; \
            if (!(AV & 4)) pack_q<ODD>(acc, Q); \
            pack_kv<ODD, 0>(acc, K, V); \
            _Pragma("unroll") for (int h = 0; h < 4; h++) { \
                const int bx = BX(h), by = bx + 1, bz = BZ(h); \
                if (h & 1) { qz[h][0] = Q[bz][0] - qz[h & 2][0]; qz[h][1] = Q[bz][1] - qz[h & 2][1]; } \
                else { qz[h][0] = imul(Q[bz][0], qlo); qz[h][1] = imul(Q[bz][1], qlo); } \
                float sm_[4] = {0.f, 0.f, 0.f, 0.f}, sn[4] = {0.f, 0.f, 0.f, 0.f}; \
                mma16(sm_, Q[bx][0], Q[bx][1], Q[by][0], Q[by][1], K[bx][0], K[by][0]); \
                mma16(sn, Q[bx][0], Q[bx][1], Q[by][0], Q[by][1], K[bx][1], K[by][1]); \
                mma8(sm_, qz[h][0], qz[h][1], K[bz][0]); mma8(sn, qz[h][0], qz[h][1], K[bz][1]); \
                l[h][0] = fmaf(sm_[0], fb[0], b00); l[h][1] = fmaf(sm_[1], fb[1], b01); \
                const float l2 = fmaf(sm_[2], fa[2], sn[2] * fb[2]), l3 = fmaf(sm_[3], fa[3], sn[3] * fb[3]); \
                float m1 = fmaxf(l2, l3); \
                m1 = fmaxf(m1, shfl_x(m1, 1)); m1 = fmaxf(m1, shfl_x(m1, 2)); \
                const float e2 = ex2(l2 - m1), e3 = ex2(l3 - m1); \
                eh[h] = pack_bf16(e2, e3); ph[h] = pack_bf16(e2 * k10, e3 * k11); \
                asm volatile("" : "+r"(eh[h]), "+r"(ph[h]) :: "memory"); \
            } } while (0)
#define PACK_Q_EARLY(ODD) do { if (AV & 4) { sched_fence(); pack_q<ODD>(acc, Q); _Pragma("unroll") for (int b = 0; b < 10; b++) asm volatile("" : "+r"(Q[b][0]), "+r"(Q[b][1]) :: "memory"); } } while (0)
        if (AV & 1) {
            if (odd) { pack_kv<1, 1>(acc, K, V); SEND(); PACK_Q_EARLY(1); RECV(); if (AV & 8) sched_fence(); OWN_KEYS(1); }
            else { pack_kv<0, 1>(acc, K, V); SEND(); PACK_Q_EARLY(0); RECV(); if (AV & 8) sched_fence(); OWN_KEYS(0); }
        } else {
            if (odd) { pack_kv<1, 1>(acc, K, V); SEND(); PACK_Q_EARLY(1); } else { pack_kv<0, 1>(acc, K, V); SEND(); PACK_Q_EARLY(0); }
            ATS(1);
            RECV();
            ATS(2);
            if (odd) OWN_KEYS(1); else OWN_KEYS(0);
        }
        ATS(3);
        if (far) {
            unsigned spins = 0;
            while (__any_sync(0xffffffffu, max(max(max(rcv[0].x, rcv[1].x), max(rcv[2].x, rcv[3].x)), rcv[4].x) == EMPTY_WORD) && ++spins < SPIN_MAX) {
#pragma unroll
                for (int i = 0; i < 5; i++) rcv[i] = ld_relaxed_v4(hg + i * 32);
            }
        }
        Kp[0] = rcv[0].x; Kp[1] = rcv[0].y; Kp[3] = rcv[0].z; Kp[4] = rcv[0].w; Kp[5] = rcv[1].x; Kp[6] = rcv[1].y; Kp[8] = rcv[1].z; Kp[9] = rcv[1].w;
        Kp[2] = rcv[2].x; Kp[7] = rcv[2].y; Vp[0] = rcv[2].z; Vp[1] = rcv[2].w; Vp[2] = rcv[3].x; Vp[3] = rcv[3].y; Vp[4] = rcv[3].z; Vp[5] = rcv[3].w;
        Vp[6] = rcv[4].x; Vp[7] = rcv[4].y; Vp[8] = rcv[4].z; Vp[9] = rcv[4].w;
        ATS(4);
        if (tid == 0) TL(4);
        if (tid == 128) TL(5);
        uint32_t* ob = reinterpret_cast<uint32_t*>(&sc->o[m][0][g][warp * 32]) + lane;
        uint32_t of[10][2];
#define PUBLISH(t) do { st_relaxed_u32(ob + (t) * 8192, of[2 * (t)][0]); st_relaxed_u32(ob + (t) * 8192 + 32, of[2 * (t) + 1][0]); \
            st_relaxed_u32(ob + (t) * 8192 + 64, of[2 * (t)][1]); st_relaxed_u32(ob + (t) * 8192 + 96, of[2 * (t) + 1][1]); \
            if (lane == 0) mbar_arrive(bars + (BAR_PA + (t)) * 8); } while (0)
#define FRONT(h) do { \
            float sp[4] = {0.f, 0.f, 0.f, 0.f}; \
            mma16(sp, Q[BX(h)][0], Q[BX(h)][1], Q[BX(h) + 1][0], Q[BX(h) + 1][1], Kp[BX(h)], Kp[BX(h) + 1]); \
            mma8(sp, qz[h][0], qz[h][1], Kp[BZ(h)]); \
            l[h][0] = fmaf(sp[0], fa[0], l[h][0]); l[h][1] = fmaf(sp[1], fa[1], l[h][1]); \
            float m0 = fmaxf(l[h][0], l[h][1]); \
            m0 = fmaxf(m0, shfl_x(m0, 1)); m0 = fmaxf(m0, shfl_x(m0, 2)); \
            l[h][0] -= m0; l[h][1] -= m0; } while (0)
#define BACK(h) do { \
            const float e0 = ex2(l[h][0]), e1 = ex2(l[h][1]); \
            float sum[4] = {0.f, 0.f, 0.f, 0.f}, O[3][4]; \
            mma8(sum, pack_bf16(e0, e1), eh[h], 0x3f803f80u); \
            const uint32_t pl = pack_bf16(e0 * k00, e1 * k01); \
            const uint32_t a0 = MSK(pl, mdn), a1 = MSK(ph[h], mup), a3 = MSK(ph[h], mdn), ap = MSK(pl, mup); \
            const float i0 = rcp(sum[0]), i1 = rcp(sum[2]); \
            _Pragma("unroll") for (int b = 0; b < 3; b++) { \
                const int bb = b < 2 ? BX(h) + b : BZ(h); \
                O[b][0] = O[b][1] = O[b][2] = O[b][3] = 0.f; \
                mma16(O[b], a0, a1, 0u, a3, V[bb][0], V[bb][1]); mma8(O[b], ap, 0u, Vp[bb]); \
                const uint32_t o0 = pack_bf16(O[b][0] * i0, O[b][1] * i0), o1 = pack_bf16(O[b][2] * i1, O[b][3] * i1); \
                of[bb][0] = (b == 2 && ((h) & 1) && c < 2) ? of[bb][0] : o0; of[bb][1] = (b == 2 && ((h) & 1) && c < 2) ? of[bb][1] : o1; \
            } } while (0)
#define HOLD_L(h) asm volatile("" : "+f"(l[h][0]), "+f"(l[h][1]) :: "memory")
#define HOLD_K(h) asm volatile("" : "+r"(Kp[BX(h)]) :: "memory")
#define PA() do { if (tid == 0) TL(6); if (tid == 128) TL(8); } while (0)
        FRONT(0); FRONT(1); BACK(0); PUBLISH(0); PA(); sched_fence(); HOLD_L(1); HOLD_K(2); HOLD_K(3); FRONT(2); FRONT(3); BACK(1); PUBLISH(1); sched_fence(); HOLD_L(2); HOLD_L(3); BACK(2); PUBLISH(2); BACK(3);
        if (tid == 0) TL(7);
        if (tid == 128) TL(9);
#define TRK 4
        float acc2[40];
#pragma unroll
        for (int i = 0; i < 40; i++) asm volatile("" : "=f"(acc2[i]));
        uint32_t gate[5][4];
        if ((TRK <= 1 || TRK == 4) && SPLIT != 3) PUBLISH(2);
        if (TRK == 0) { PUBLISH(3); PUBLISH(4); }
        const float2 su0 = lds_f2(stb + (8 + r) * 8), su1 = lds_f2(stb + (16 + r) * 8);
        const float rh0 = bfr(0.5f * su0.y), rh1 = bfr(0.5f * su1.y);
        const uint32_t gm[2] = {dup_hi(su0.x), dup_hi(su1.x)}, gh[2] = {dup_hi(rh0), dup_hi(rh1)};
        const uint32_t gl[2] = {pack_bf16(0.5f * su0.y - rh0, 0.5f * su0.y - rh0), pack_bf16(0.5f * su1.y - rh1, 0.5f * su1.y - rh1)};
        mbar_wait(bars + BAR_WO * 8, 0);
        bar_sync<4, 256>();
        if (tid == 0) TL(13);
        const uint32_t wlo = ((sb + SM_WO) & 0x3ffffu) >> 4, alo = (((sb + p * 2048) & 0x3ffffu) >> 4) | (8u << 16);
        uint32_t wd_[8];
#pragma unroll
        for (int i = 0; i < 8; i++) wd_[i] = wlo + (7 - i) * 640 + (((SM_WT - SM_WO - (7 - i) * 10240 + (SRC(i) & 1) * 10240 + (SRC(i) >> 1) * 32) >> 4) << 16);
        wg_fence();
#pragma unroll
        for (int t = 0; t < 5; t++) wgmma_rs_n80(acc2, of[2 * t][0], of[2 * t][1], of[2 * t + 1][0], of[2 * t + 1][1], wd_[0] + t * 128, t != 0);
        wg_commit();
#define NG0 5
#define GATES(t) do { _Pragma("unroll") for (int e = 0; e < 4; e++) {        \
                const uint32_t d = hsub2(xs[t][e], gm[e & 1]), h2 = hfma2(d, gh[e & 1], hmul2(d, gl[e & 1]));        \
                const float a = bf_lo(h2), b = bf_hi(h2); \
                gate[t][e] = pack_bf16(fmaf(a, tanh_f(a), a), fmaf(b, tanh_f(b), b)); \
                asm volatile("" : "+r"(gate[t][e]) :: "memory"); } } while (0)
        GATES(0);
        if (TRK == 4) { sched_fence(); PUBLISH(3); }
        if (TRK && TRK < 4) {
            mbar_wait(bars + BAR_GI * 8, 0);
            if (TRK >= 2 && SPLIT != 3) PUBLISH(2);
            if (TRK <= 2) { PUBLISH(3); PUBLISH(4); }
        }
#pragma unroll
        for (int t = 1; t < NG0; t++) GATES(t);
        if (TRK == 4) { sched_fence(); PUBLISH(4); }
        if (tid == 0) TL(12);
#pragma unroll
        for (int t = 0; t < 5; t++) {
            const uint32_t ad = alo + ((t == 2 ? SM_O2 : ((t == 0 || t == 3) ? SM_O0 : SM_O1)) >> 4);
            mbar_spin(bars + (BAR_OF + t) * 8, 0);
            if (STAG < 5 && t == STAG && p == 1) bar_sync<5, 256>();
            if (TRK == 3 && t == 0) { PUBLISH(3); PUBLISH(4); }
            wg_fence();
#pragma unroll
            for (int i = 0; i < 7; i++) {
                wgmma_ss_n80(acc2, ad + i * 256, wd_[i + 1] + t * 128);
                if (i == 0 && (t == 1 || t == 2)) {
                    wg_commit(); wg_wait<1>();
                    if ((tid & 127) == 0) mbar_arrive(bars + (BAR_OE + t + 1) * 8);
                }
                if (STAG < 5 && i == 4 && t == 4 && p == 0) asm volatile("bar.arrive 5, 256;" ::: "memory");
            }
            wg_commit();
            if (t + NG0 < 5) GATES(t + NG0);
        }
        const int wrow = m * 128 + 32 * w + p;
        {
            mbar_wait(bars + BAR_SEL * 8, 0);
            const uint2 sel = lds_v2(sb + SM_TOP);
            const unsigned d0 = sel.x - wrow, d1 = sel.y - wrow;
            if ((d0 & ~30u) == 0 || (d1 & ~30u) == 0) {
                mbar_wait(bars + BAR_Y * 8, 0);
#pragma unroll
                for (int h = 0; h < 2; h++) {
                    const unsigned me = 2 * r + 16 * h;
                    if (d0 == me || d1 == me) {
#pragma unroll
                        for (int t = 0; t < 5; t++) {
                            const uint32_t a = sb + SM_GT + (d0 == me ? 0 : 160) + (t < 4 ? t + odd : 4 - 4 * odd) * 32 + c * 4;
                            gate[t][h] = lds_u32(a); gate[t][2 + h] = lds_u32(a + 16);
                        }
                    }
                }
                __syncwarp();
            }
        }
        const uint32_t ssb = sb + (warp < 6 ? SM_EX : SM_G7 - 6 * 2560) + warp * 2560;
        const uint32_t laddr = ssb + (lane & 15) * 160 + (lane >> 4) * 16;
        wg_wait<0>();
        if (tid == 0) TL(1);
        if (tid == 128) TL(14);
        if (__any_sync(0xffffffffu, acc2[0] != acc2[0] || acc2[2] != acc2[2])) {
#pragma unroll
            for (int i = 0; i < 40; i++) acc2[i] = 0.f;
            const int krow = lane & 15;
#pragma unroll 1
            for (int ks = 0; ks < 40; ks++) {
                const int i = ks / 5;
                const uint32_t* src = ob + (ks - 5 * i) * 8192 + (SRC(i) - g) * 1024;
                uint32_t a0, a1, a2, a3; unsigned spins = 0;
                do { a0 = ld_relaxed_u32(src); a2 = ld_relaxed_u32(src + 32); a1 = ld_relaxed_u32(src + 64); a3 = ld_relaxed_u32(src + 96); }
                while (__any_sync(0xffffffffu, max(max(a0, a1), max(a2, a3)) == EMPTY_WORD) && ++spins < SPIN_MAX);
#pragma unroll
                for (int nb = 0; nb < 5; nb++) {
                    uint32_t b[4];
                    ldsm4t(sb + (nb < 4 ? SM_WO + (35 + ks - 10 * i) * 2048 : SM_WT + ((SRC(i) & 1) * 5 + ks - 5 * i) * 2048) + krow * 128 + (((2 * (nb < 4 ? nb : SRC(i) >> 1) + (lane >> 4)) ^ (krow & 7)) << 4), b);
                    mma16(*reinterpret_cast<float (*)[4]>(&acc2[8 * nb]), a0, a1, a2, a3, b[0], b[1]);
                    mma16(*reinterpret_cast<float (*)[4]>(&acc2[8 * nb + 4]), a0, a1, a2, a3, b[2], b[3]);
                }
            }
        }
#pragma unroll
        for (int t = 0; t < 5; t++) {
            uint32_t o[4];
#pragma unroll
            for (int e = 0; e < 4; e++) o[e] = hadd2(xs[t][e], hmul2(pack_bf16(acc2[8 * t + 2 * e], acc2[8 * t + 2 * e + 1]), gate[t][e]));
            stsm4(laddr + (t < 4 ? t + odd : 4 - 4 * odd) * 32, o[0], o[1], o[2], o[3]);
        }
        asm volatile("fence.proxy.async.shared::cta;" ::: "memory");
        __syncwarp();
        if (elect_one()) tma3d_store(&tm_o, ssb, g * 80, m * 64 + w * 16, p);
    }
}

typedef CUresult (*EncodeFn)(CUtensorMap*, CUtensorMapDataType, cuuint32_t, void*, const cuuint64_t*, const cuuint64_t*, const cuuint32_t*,
                             const cuuint32_t*, CUtensorMapInterleave, CUtensorMapSwizzle, CUtensorMapL2promotion, CUtensorMapFloatOOBfill);

static void encode(EncodeFn enc, CUtensorMap* tm, const void* ptr, int rank, uint64_t d0, uint64_t d1, uint64_t d2, uint64_t s1, uint64_t s2,
                   uint32_t b0, uint32_t b1, uint32_t b2, CUtensorMapSwizzle swz) {
    cuuint64_t dims[3] = {d0, d1, d2}, strides[2] = {s1, s2};
    cuuint32_t box[3] = {b0, b1, b2}, es[3] = {1, 1, 1};
    enc(tm, CU_TENSOR_MAP_DATA_TYPE_BFLOAT16, rank, const_cast<void*>(ptr), dims, strides, box, es, CU_TENSOR_MAP_INTERLEAVE_NONE, swz,
        CU_TENSOR_MAP_L2_PROMOTION_L2_128B, CU_TENSOR_MAP_FLOAT_OOB_FILL_NONE);
}

}

extern "C" void kernel_launch(void* const* d_in, const int* in_sizes, int n_in, void* d_out, int out_size) {
    using namespace fk;
    (void)in_sizes; (void)n_in; (void)out_size;
    const __nv_bfloat16* x = (const __nv_bfloat16*)d_in[0];
    const __nv_bfloat16* wqkv = (const __nv_bfloat16*)d_in[1];
    const __nv_bfloat16* wo = (const __nv_bfloat16*)d_in[2];
    const __nv_bfloat16* wr = (const __nv_bfloat16*)d_in[4];
    const __nv_bfloat16* wg = (const __nv_bfloat16*)d_in[5];
    const __nv_bfloat16* wu = (const __nv_bfloat16*)d_in[6];
    const __nv_bfloat16* wd = (const __nv_bfloat16*)d_in[7];
    static EncodeFn enc = nullptr;
    static Scratch* scratch = nullptr;
    static Roles roles; static int by_sm = 0;
    if (!enc) {
        void* fn = nullptr; cudaDriverEntryPointQueryResult qr;
        cudaGetDriverEntryPoint("cuTensorMapEncodeTiled", &fn, cudaEnableDefault, &qr);
        enc = (EncodeFn)fn;
        cudaFuncSetAttribute(fused_kernel, cudaFuncAttributeMaxDynamicSharedMemorySize, SM_TOTAL);
        cudaGetSymbolAddress((void**)&scratch, g_scratch);
        int dev = 0, nsm = 0;
        cudaGetDevice(&dev); cudaDeviceGetAttribute(&nsm, cudaDevAttrMultiProcessorCount, dev);
        by_sm = nsm == NCTA + NIDLE;
        roles.k16 = 0x10000; roles.zero = 0;
        for (int t = 0; t < 66; t++) roles.pair[t] = t < 32 ? (t & 7) * 8 + (t >> 3) : (t < 60 ? (1 + (t - 32) % 7) * 8 + 4 + (t - 32) / 7 : (t < 62 ? t + 4 : t - 58));
    }
    CUtensorMap tx, tw, twt, two, twn, td, tg, tu, to;
    encode(enc, &tx, x, 3, 640, 1024, 2, 2560, 1280, 64, 64, 2, CU_TENSOR_MAP_SWIZZLE_128B);
    encode(enc, &tw, wqkv, 3, 640, 640, 3, 3840, 1280, 64, 32, 3, CU_TENSOR_MAP_SWIZZLE_128B);
    encode(enc, &twt, wqkv, 3, 640, 640, 3, 3840, 1280, 16, 32, 3, CU_TENSOR_MAP_SWIZZLE_32B);
    encode(enc, &two, wo, 2, 640, 640, 1, 1280, 0, 64, 80, 1, CU_TENSOR_MAP_SWIZZLE_128B);
    encode(enc, &twn, wo, 3, 640, 4, 160, 160 * 1280, 1280, 16, 4, 160, CU_TENSOR_MAP_SWIZZLE_NONE);
    encode(enc, &td, wd, 2, 640, 1728, 1, 1280, 0, 64, 32, 1, CU_TENSOR_MAP_SWIZZLE_128B);
    encode(enc, &to, d_out, 3, 640, 1024, 2, 2560, 1280, 80, 16, 1, CU_TENSOR_MAP_SWIZZLE_NONE);
    encode(enc, &tg, wg, 2, 1728, 640, 1, 3456, 0, 32, 80, 1, CU_TENSOR_MAP_SWIZZLE_64B);
    encode(enc, &tu, wu, 2, 1728, 640, 1, 3456, 0, 32, 80, 1, CU_TENSOR_MAP_SWIZZLE_64B);
    fused_kernel<<<NCTA + NIDLE, NTHREADS, SM_TOTAL>>>(scratch, x, wqkv, wo, wr, wd, (__nv_bfloat16*)d_out, by_sm, roles, tx, tw, twt, two, twn, td, tg, tu, to);
}
```

```cpp
#include <cuda_runtime.h>
#include <cuda_bf16.h>
#include <cuda.h>
#include <stdint.h>

#define DEVI __device__ __forceinline__

namespace fk {

constexpr int DM = 640;
constexpr int NCTA = 128, NIDLE = 4, NTHREADS = 512;
constexpr int NMOE = 54;
constexpr int STAGE = 47104;
constexpr int OFF_B = 16384, B_HALF = 15360;
constexpr int SM_DW = 0;
constexpr int SM_WO = 33792;
constexpr int SM_G7 = SM_WO + 81920;
constexpr int SM_WT = SM_G7 + 5120;
constexpr int SM_EX = 3 * STAGE;
constexpr int SM_O0 = 3 * STAGE + OFF_B, SM_O1 = 4 * STAGE, SM_O2 = SM_DW;
constexpr int SM_MW = 4 * STAGE;
constexpr int SM_BX = SM_MW + 35840;
constexpr int SM_XSEL = SM_BX + 2560;
constexpr int SM_ST = SM_XSEL + 2592;
constexpr int SM_GT = SM_ST + 1152;
constexpr int SM_H = SM_GT + 320;
constexpr int SM_TOP = SM_XSEL + 1280;
constexpr int SM_TAG = SM_H + 128;
constexpr int SM_BAR = SM_TAG + 16;
constexpr int SM_TL = SM_BAR + 416;
constexpr int SM_TOTAL = SM_TL;
static_assert(SM_TOTAL <= 232448 && SM_BAR % 8 == 0 && SM_XSEL % 16 == 0 && SM_ST % 16 == 0 && SM_GT % 16 == 0 && SM_BX % 1024 == 0 && SM_TOP % 16 == 0, "smem layout");
constexpr int BAR_FULL = 0, BAR_EMPTY = 4, BAR_WR = 8, BAR_Y = 9, BAR_GW = 10, BAR_DW = 11, BAR_PX = 12, BAR_RS = 13, BAR_SEL = 14, BAR_GI = 15, BAR_CX = 42, BAR_PG = 43, BAR_WT = 44, BAR_GO = 45, BAR_TB = 46  , BAR_AN = 49, BAR_W2 = 50,
              BAR_OF = 16  , BAR_OE = 21  , BAR_WO = 25, BAR_CS = 26, BAR_PA = 27  , BAR_AE = 32  , BAR_FA = 38  , NBAR = 51;
#define POLL_NS 100
#define PF1_NS 200
#define STAG 3
#define GP0 3
#define DP0 99
constexpr uint32_t EMPTY_WORD = 0xffffffffu;
struct Roles { unsigned k16, zero; unsigned short pair[NCTA / 2 + NIDLE / 2]; };
constexpr unsigned SPIN_MAX = 1u << 20;

struct Outbox {
    uint4 msg[192];
    uint4 gt[2][32];
};
struct Scratch {
    uint4 o[16][5][8][256];
    uint4 halo[NCTA][320];
    Outbox box[NIDLE];
    uint4 cs[8][8][2][32];
    uint4 yp[8][56][32];
    uint2 rowinfo[16][2][64];
    unsigned flag[NCTA][8];
    unsigned open[NIDLE][32];
    unsigned epoch[(NCTA + NIDLE) * 32];
};
__device__ Scratch g_scratch;
#define TL(i) do { } while (0)
#define GT(i) do { } while (0)

DEVI uint32_t smem_u32(const void* p) { return (uint32_t)__cvta_generic_to_shared(p); }
DEVI void mbar_init(uint32_t bar, uint32_t cnt) { asm volatile("mbarrier.init.shared::cta.b64 [%0], %1;" :: "r"(bar), "r"(cnt)); }
DEVI void mbar_expect_tx(uint32_t bar, uint32_t bytes) { asm volatile("mbarrier.arrive.expect_tx.shared::cta.b64 _, [%0], %1;" :: "r"(bar), "r"(bytes) : "memory"); }
DEVI void mbar_arrive(uint32_t bar) { asm volatile("mbarrier.arrive.shared::cta.b64 _, [%0];" :: "r"(bar) : "memory"); }
DEVI uint32_t clk32() { uint32_t t; asm volatile("mov.u32 %0, %%clock;" : "=r"(t) :: "memory"); return t; }
DEVI void sched_fence() { asm volatile("pmevent 0;" ::: "memory"); }
DEVI bool mbar_try(uint32_t bar, uint32_t parity) {
    uint32_t ok;
    asm volatile("{\n.reg .pred p;\nmbarrier.try_wait.parity.shared::cta.b64 p, [%1], %2, 0x989680;\nselp.u32 %0, 1, 0, p;\n}" : "=r"(ok) : "r"(bar), "r"(parity) : "memory");
    return ok != 0;
}
DEVI void mbar_wait(uint32_t bar, uint32_t parity) {
    while (!mbar_try(bar, parity)) { }
}
DEVI void mbar_spin(uint32_t bar, uint32_t parity) {
    uint32_t ok;
    do { asm volatile("{\n.reg .pred p;\nmbarrier.try_wait.parity.shared::cta.b64 p, [%1], %2;\nselp.u32 %0, 1, 0, p;\n}" : "=r"(ok) : "r"(bar), "r"(parity) : "memory"); } while (!ok);
}
DEVI bool elect_one() {
    uint32_t p;
    asm volatile("{\n.reg .pred P;\nelect.sync _|P, 0xffffffff;\nselp.u32 %0, 1, 0, P;\n}" : "=r"(p));
    return p != 0;
}
DEVI void tma3d(uint32_t dst, const CUtensorMap* tm, uint32_t bar, int c0, int c1, int c2) {
    asm volatile("cp.async.bulk.tensor.3d.shared::cluster.global.mbarrier::complete_tx::bytes [%0], [%1, {%3, %4, %5}], [%2];"
                 :: "r"(dst), "l"(tm), "r"(bar), "r"(c0), "r"(c1), "r"(c2) : "memory");
}
DEVI void tma3d_mc(uint32_t dst, const CUtensorMap* tm, uint32_t bar, int c0, int c1, int c2) {
    asm volatile("cp.async.bulk.tensor.3d.shared::cluster.global.mbarrier::complete_tx::bytes.multicast::cluster [%0], [%1, {%3, %4, %5}], [%2], %6;"
                 :: "r"(dst), "l"(tm), "r"(bar), "r"(c0), "r"(c1), "r"(c2), "h"((uint16_t)3) : "memory");
}
DEVI void tma2d(uint32_t dst, const CUtensorMap* tm, uint32_t bar, int c0, int c1) {
    asm volatile("cp.async.bulk.tensor.2d.shared::cluster.global.mbarrier::complete_tx::bytes [%0], [%1, {%3, %4}], [%2];"
                 :: "r"(dst), "l"(tm), "r"(bar), "r"(c0), "r"(c1) : "memory");
}
DEVI void tma2d_prefetch(const CUtensorMap* tm, int c0, int c1) {
    asm volatile("cp.async.bulk.prefetch.tensor.2d.L2.global [%0, {%1, %2}];" :: "l"(tm), "r"(c0), "r"(c1) : "memory");
}
DEVI void tma2d_mc(uint32_t dst, const CUtensorMap* tm, uint32_t bar, int c0, int c1) {
    asm volatile("cp.async.bulk.tensor.2d.shared::cluster.global.mbarrier::complete_tx::bytes.multicast::cluster [%0], [%1, {%3, %4}], [%2], %5;"
                 :: "r"(dst), "l"(tm), "r"(bar), "r"(c0), "r"(c1), "h"((uint16_t)3) : "memory");
}
DEVI void mbar_arrive_both(uint32_t bar) {
    asm volatile("{\n.reg .b32 ra;\nmapa.shared::cluster.u32 ra, %0, 0;\nmbarrier.arrive.shared::cluster.b64 _, [ra];\n"
                 "mapa.shared::cluster.u32 ra, %0, 1;\nmbarrier.arrive.shared::cluster.b64 _, [ra];\n}" :: "r"(bar) : "memory");
}
DEVI void mbar_arrive_at(uint32_t bar, uint32_t cta) {
    asm volatile("{\n.reg .b32 ra;\nmapa.shared::cluster.u32 ra, %0, %1;\nmbarrier.arrive.shared::cluster.b64 _, [ra];\n}" :: "r"(bar), "r"(cta) : "memory");
}
DEVI void st_halo(bool global, void* pg, uint32_t ps, uint32_t a, uint32_t b, uint32_t c, uint32_t d) {
    asm volatile("{\n.reg .pred p;\nsetp.ne.b32 p, %0, 0;\n@p st.relaxed.gpu.global.v4.u32 [%1], {%3,%4,%5,%6};\n@!p st.shared.v4.u32 [%2], {%3,%4,%5,%6};\n}"
                 :: "r"((uint32_t)global), "l"(pg), "r"(ps), "r"(a), "r"(b), "r"(c), "r"(d) : "memory");
}
DEVI uint4 ld_halo(bool global, const void* pg, uint32_t ps) {
    uint4 v;
    asm volatile("{\n.reg .pred p;\nsetp.ne.b32 p, %4, 0;\n@p ld.relaxed.gpu.global.v4.u32 {%0,%1,%2,%3}, [%5];\n@!p ld.shared.v4.u32 {%0,%1,%2,%3}, [%6];\n}"
                 : "=r"(v.x), "=r"(v.y), "=r"(v.z), "=r"(v.w) : "r"((uint32_t)global), "l"(pg), "r"(ps) : "memory");
    return v;
}
DEVI void ldg_if(bool on, const void* pg, uint4& v) {
    asm volatile("{\n.reg .pred p;\nsetp.ne.b32 p, %4, 0;\n@p ld.relaxed.gpu.global.v4.u32 {%0,%1,%2,%3}, [%5];\n}"
                 : "+r"(v.x), "+r"(v.y), "+r"(v.z), "+r"(v.w) : "r"((uint32_t)on), "l"(pg) : "memory");
}
DEVI void bar_sync_id(int id, int n) { asm volatile("bar.sync %0, %1;" :: "r"(id), "r"(n) : "memory"); }
DEVI void st_async_peer(uint32_t addr, uint32_t bar, uint32_t peer, uint32_t v) {
    asm volatile("{\n.reg .b32 ra, rb;\nmapa.shared::cluster.u32 ra, %0, %2;\nmapa.shared::cluster.u32 rb, %1, %2;\n"
                 "st.async.weak.shared::cluster.mbarrier::complete_tx::bytes.b32 [ra], %3, [rb];\n}" :: "r"(addr), "r"(bar), "r"(peer), "r"(v) : "memory");
}
DEVI void st_async_v2(uint32_t addr, uint32_t bar, uint32_t cta, float a, float b) {
    asm volatile("{\n.reg .b32 ra, rb;\nmapa.shared::cluster.u32 ra, %0, %2;\nmapa.shared::cluster.u32 rb, %1, %2;\n"
                 "st.async.weak.shared::cluster.mbarrier::complete_tx::bytes.v2.f32 [ra], {%3,%4}, [rb];\n}" :: "r"(addr), "r"(bar), "r"(cta), "f"(a), "f"(b) : "memory");
}
DEVI void st_async_v4(uint32_t addr, uint32_t bar, uint32_t cta, float a, float b, float c, float d) {
    asm volatile("{\n.reg .b32 ra, rb;\nmapa.shared::cluster.u32 ra, %0, %2;\nmapa.shared::cluster.u32 rb, %1, %2;\n"
                 "st.async.weak.shared::cluster.mbarrier::complete_tx::bytes.v4.f32 [ra], {%3,%4,%5,%6}, [rb];\n}" :: "r"(addr), "r"(bar), "r"(cta), "f"(a), "f"(b), "f"(c), "f"(d) : "memory");
}
DEVI void bulk_load(uint32_t dst, const void* src, uint32_t bytes, uint32_t bar) {
    asm volatile("cp.async.bulk.shared::cluster.global.mbarrier::complete_tx::bytes [%0], [%1], %2, [%3];" :: "r"(dst), "l"(src), "r"(bytes), "r"(bar) : "memory");
}
DEVI void cluster_arrive() { asm volatile("barrier.cluster.arrive.relaxed.aligned;" ::: "memory"); }
DEVI void cluster_wait() { asm volatile("barrier.cluster.wait.aligned;" ::: "memory"); }
DEVI void wg_fence() { asm volatile("wgmma.fence.sync.aligned;" ::: "memory"); }
DEVI void wg_commit() { asm volatile("wgmma.commit_group.sync.aligned;" ::: "memory"); }
template <int N> DEVI void wg_wait() { asm volatile("wgmma.wait_group.sync.aligned %0;" :: "n"(N) : "memory"); }
template <int ID, int N> DEVI void bar_sync() { asm volatile("bar.sync %0, %1;" :: "n"(ID), "n"(N) : "memory"); }
DEVI void spin_guard(unsigned& n) { if (++n > SPIN_MAX) __trap(); }
DEVI uint4 ld_relaxed_v4(const void* p) {
    uint4 v;
    asm volatile("ld.relaxed.gpu.global.v4.u32 {%0,%1,%2,%3}, [%4];" : "=r"(v.x), "=r"(v.y), "=r"(v.z), "=r"(v.w) : "l"(p) : "memory");
    return v;
}
DEVI void st_relaxed_v4(void* p, const uint4& v) {
    asm volatile("st.relaxed.gpu.global.v4.u32 [%0], {%1,%2,%3,%4};" :: "l"(p), "r"(v.x), "r"(v.y), "r"(v.z), "r"(v.w) : "memory");
}
DEVI unsigned ld_relaxed_u32(const void* p) { unsigned v; asm volatile("ld.relaxed.gpu.global.u32 %0, [%1];" : "=r"(v) : "l"(p) : "memory"); return v; }
DEVI unsigned ld_acquire_u32(const void* p) { unsigned v; asm volatile("ld.acquire.gpu.global.u32 %0, [%1];" : "=r"(v) : "l"(p) : "memory"); return v; }
DEVI void st_relaxed_u32(void* p, unsigned v) { asm volatile("st.relaxed.gpu.global.u32 [%0], %1;" :: "l"(p), "r"(v) : "memory"); }
DEVI void st_relaxed_v2(void* p, unsigned a, unsigned b) { asm volatile("st.relaxed.gpu.global.v2.u32 [%0], {%1,%2};" :: "l"(p), "r"(a), "r"(b) : "memory"); }
DEVI uint4 ld_gen_v4(const void* p) {
    uint4 v;
    asm volatile("ld.relaxed.gpu.v4.u32 {%0,%1,%2,%3}, [%4];" : "=r"(v.x), "=r"(v.y), "=r"(v.z), "=r"(v.w) : "l"(p) : "memory");
    return v;
}
DEVI void st_gen_v4(void* p, const uint4& v) { asm volatile("st.relaxed.gpu.v4.u32 [%0], {%1,%2,%3,%4};" :: "l"(p), "r"(v.x), "r"(v.y), "r"(v.z), "r"(v.w) : "memory"); }
DEVI float sqrt_approx(float x) { float y; asm("sqrt.approx.ftz.f32 %0, %1;" : "=f"(y) : "f"(x)); return y; }
DEVI void red_add_u32(unsigned* p, unsigned v) { asm volatile("red.relaxed.gpu.global.add.u32 [%0], %1;" :: "l"(p), "r"(v) : "memory"); }
DEVI void red_add_v4(void* p, float a, float b, float c, float d) {
    asm volatile("red.relaxed.gpu.global.add.v4.f32 [%0], {%1,%2,%3,%4};" :: "l"(p), "f"(a), "f"(b), "f"(c), "f"(d) : "memory");
}
DEVI float4 ld_relaxed_f4(const void* p) {
    float4 v;
    asm volatile("ld.relaxed.gpu.global.v4.f32 {%0,%1,%2,%3}, [%4];" : "=f"(v.x), "=f"(v.y), "=f"(v.z), "=f"(v.w) : "l"(p) : "memory");
    return v;
}
DEVI void tma3d_store(const CUtensorMap* tm, uint32_t src, int c0, int c1, int c2) {
    asm volatile("cp.async.bulk.tensor.3d.global.shared::cta.bulk_group [%0, {%2, %3, %4}], [%1];\ncp.async.bulk.commit_group;\ncp.async.bulk.wait_group.read 0;"
                 :: "l"(tm), "r"(src), "r"(c0), "r"(c1), "r"(c2) : "memory");
}
DEVI uint32_t lds_u16(uint32_t a) { unsigned short v; asm volatile("ld.shared.u16 %0, [%1];" : "=h"(v) : "r"(a)); return v; }
DEVI void fence_gpu() { asm volatile("fence.acq_rel.gpu;" ::: "memory"); }
DEVI uint4 ldg_v4(const void* p) {
    uint4 v;
    asm volatile("ld.global.L1::no_allocate.v4.u32 {%0,%1,%2,%3}, [%4];" : "=r"(v.x), "=r"(v.y), "=r"(v.z), "=r"(v.w) : "l"(p) : "memory");
    return v;
}
DEVI uint4 lds_v4(uint32_t a) { uint4 v; asm volatile("ld.shared.v4.u32 {%0,%1,%2,%3}, [%4];" : "=r"(v.x), "=r"(v.y), "=r"(v.z), "=r"(v.w) : "r"(a)); return v; }
DEVI void sts_v4(uint32_t a, const uint4& v) { asm volatile("st.shared.v4.u32 [%0], {%1,%2,%3,%4};" :: "r"(a), "r"(v.x), "r"(v.y), "r"(v.z), "r"(v.w) : "memory"); }
DEVI void sts_f4(uint32_t a, float x, float y, float z, float w) { asm volatile("st.shared.v4.f32 [%0], {%1,%2,%3,%4};" :: "r"(a), "f"(x), "f"(y), "f"(z), "f"(w) : "memory"); }
DEVI float2 lds_f2(uint32_t a) { float2 v; asm volatile("ld.shared.v2.f32 {%0,%1}, [%2];" : "=f"(v.x), "=f"(v.y) : "r"(a)); return v; }
DEVI float4 lds_f4(uint32_t a) { float4 v; asm volatile("ld.shared.v4.f32 {%0,%1,%2,%3}, [%4];" : "=f"(v.x), "=f"(v.y), "=f"(v.z), "=f"(v.w) : "r"(a)); return v; }
DEVI void ldsm4(uint32_t addr, uint32_t& a, uint32_t& b, uint32_t& c, uint32_t& d) {
    asm volatile("ldmatrix.sync.aligned.m8n8.x4.shared.b16 {%0,%1,%2,%3}, [%4];" : "=r"(a), "=r"(b), "=r"(c), "=r"(d) : "r"(addr));
}
DEVI void ldsm4_if(bool on, uint32_t addr, uint32_t (&v)[4]) {
    asm volatile("{\n.reg .pred p;\nsetp.ne.b32 p, %5, 0;\n@p ldmatrix.sync.aligned.m8n8.x4.shared.b16 {%0,%1,%2,%3}, [%4];\n}"
                 : "+r"(v[0]), "+r"(v[1]), "+r"(v[2]), "+r"(v[3]) : "r"(addr), "r"((uint32_t)on));
}
DEVI void ldsm4t(uint32_t addr, uint32_t (&v)[4]) {
    asm volatile("ldmatrix.sync.aligned.m8n8.x4.trans.shared.b16 {%0,%1,%2,%3}, [%4];" : "=r"(v[0]), "=r"(v[1]), "=r"(v[2]), "=r"(v[3]) : "r"(addr));
}
DEVI void ldsm2(uint32_t addr, uint32_t& a, uint32_t& b) { asm volatile("ldmatrix.sync.aligned.m8n8.x2.shared.b16 {%0,%1}, [%2];" : "=r"(a), "=r"(b) : "r"(addr)); }
DEVI void cp_async16(uint32_t dst, const void* src) { asm volatile("cp.async.cg.shared.global [%0], [%1], 16;" :: "r"(dst), "l"(src) : "memory"); }
DEVI void prefetch_l2_bulk(const void* p, uint32_t bytes) { asm volatile("cp.async.bulk.prefetch.L2.global [%0], %1;" :: "l"(p), "r"(bytes) : "memory"); }
DEVI void sts_u16(uint32_t a, uint32_t v) { asm volatile("st.shared.u16 [%0], %1;" :: "r"(a), "h"((unsigned short)v) : "memory"); }
DEVI uint32_t hfma2(uint32_t a, uint32_t b, uint32_t c) { uint32_t d; asm("fma.rn.bf16x2 %0, %1, %2, %3;" : "=r"(d) : "r"(a), "r"(b), "r"(c)); return d; }
DEVI uint32_t imul(uint32_t a, uint32_t b) { uint32_t d; asm("mul.lo.u32 %0, %1, %2;" : "=r"(d) : "r"(a), "r"(b)); return d; }
DEVI float tanh_f(float x) { float t; asm("tanh.approx.f32 %0, %1;" : "=f"(t) : "f"(x)); return t; }
DEVI void stsm4(uint32_t addr, uint32_t a, uint32_t b, uint32_t c, uint32_t d) {
    asm volatile("stmatrix.sync.aligned.m8n8.x4.shared.b16 [%0], {%1,%2,%3,%4};" :: "r"(addr), "r"(a), "r"(b), "r"(c), "r"(d) : "memory");
}
DEVI uint32_t movm(uint32_t a) { uint32_t d; asm("movmatrix.sync.aligned.m8n8.trans.b16 %0, %1;" : "=r"(d) : "r"(a)); return d; }
DEVI void mma16(float (&c)[4], uint32_t a0, uint32_t a1, uint32_t a2, uint32_t a3, uint32_t b0, uint32_t b1) {
    asm("mma.sync.aligned.m16n8k16.row.col.f32.bf16.bf16.f32 {%0,%1,%2,%3}, {%4,%5,%6,%7}, {%8,%9}, {%0,%1,%2,%3};"
                 : "+f"(c[0]), "+f"(c[1]), "+f"(c[2]), "+f"(c[3]) : "r"(a0), "r"(a1), "r"(a2), "r"(a3), "r"(b0), "r"(b1));
}
DEVI void mma8(float (&c)[4], uint32_t a0, uint32_t a1, uint32_t b0) {
    asm("mma.sync.aligned.m16n8k8.row.col.f32.bf16.bf16.f32 {%0,%1,%2,%3}, {%4,%5}, {%6}, {%0,%1,%2,%3};"
                 : "+f"(c[0]), "+f"(c[1]), "+f"(c[2]), "+f"(c[3]) : "r"(a0), "r"(a1), "r"(b0));
}
DEVI uint32_t pack_bf16(float lo, float hi) { uint32_t d; asm("cvt.rn.bf16x2.f32 %0, %1, %2;" : "=r"(d) : "f"(hi), "f"(lo)); return d; }
DEVI float bf_lo(uint32_t v) { return __uint_as_float(v << 16); }
DEVI float bf_hi(uint32_t v) { return __uint_as_float(v & 0xffff0000u); }
DEVI float bfr(float x) { return __bfloat162float(__float2bfloat16_rn(x)); }
DEVI uint32_t tagf(float v, unsigned tag) { return (__float_as_uint(v) & ~15u) | (tag & 15); }
DEVI float ex2(float x) { float y; asm("ex2.approx.ftz.f32 %0, %1;" : "=f"(y) : "f"(x)); return y; }
DEVI float rcp(float x) { float y; asm("rcp.approx.ftz.f32 %0, %1;" : "=f"(y) : "f"(x)); return y; }
DEVI float sigmoid_f(float x) { return rcp(1.0f + ex2(x * -1.4426950408889634f)); }
DEVI float silu_f(float x) { const float h = 0.5f * x; float t; asm("tanh.approx.f32 %0, %1;" : "=f"(t) : "f"(h)); return fmaf(h, t, h); }
DEVI uint32_t hsub2(uint32_t a, uint32_t b) { uint32_t d; asm("sub.rn.bf16x2 %0, %1, %2;" : "=r"(d) : "r"(a), "r"(b)); return d; }
DEVI uint32_t hadd2(uint32_t a, uint32_t b) { uint32_t d; asm("add.rn.bf16x2 %0, %1, %2;" : "=r"(d) : "r"(a), "r"(b)); return d; }
DEVI uint32_t hmul2(uint32_t a, uint32_t b) { uint32_t d; asm("mul.rn.bf16x2 %0, %1, %2;" : "=r"(d) : "r"(a), "r"(b)); return d; }
DEVI uint32_t dup_hi(float x) { return __byte_perm(__float_as_uint(x), 0, 0x3232); }
DEVI void sts_u32(uint32_t a, uint32_t v) { asm volatile("st.shared.u32 [%0], %1;" :: "r"(a), "r"(v) : "memory"); }
DEVI void sts_f2(uint32_t a, float x, float y) { asm volatile("st.shared.v2.f32 [%0], {%1,%2};" :: "r"(a), "f"(x), "f"(y) : "memory"); }
DEVI uint2 lds_v2(uint32_t a) { uint2 v; asm volatile("ld.shared.v2.u32 {%0,%1}, [%2];" : "=r"(v.x), "=r"(v.y) : "r"(a)); return v; }
DEVI uint32_t lds_u32(uint32_t a) { uint32_t v; asm volatile("ld.shared.u32 %0, [%1];" : "=r"(v) : "r"(a)); return v; }
DEVI float lds_f32(uint32_t a) { float v; asm volatile("ld.shared.f32 %0, [%1];" : "=f"(v) : "r"(a)); return v; }
DEVI float shfl_x(float v, int o) { return __shfl_xor_sync(0xffffffffu, v, o); }

DEVI void wgmma_rs_n192(float (&d)[120], uint32_t a0, uint32_t a1, uint32_t a2, uint32_t a3, uint32_t blo, uint32_t scale_d) {
    asm volatile("{\n.reg .b64 db;\n.reg .pred p;\n"
        "setp.ne.b32 p, %101, 0;\n"
        "mov.b64 db, {%100, 0x40000040};\n"
        "wgmma.mma_async.sync.aligned.m64n192k16.f32.bf16.bf16 "
        "{%0, %1, %2, %3, %4, %5, %6, %7, %8, %9, %10, %11, %12, %13, %14, %15, %16, %17, %18, %19, %20, %21, %22, %23, %24, %25, %26, %27, %28, %29, %30, %31, %32, %33, %34, %35, %36, %37, %38, %39, %40, %41, %42, %43, %44, %45, %46, %47, %48, %49, %50, %51, %52, %53, %54, %55, %56, %57, %58, %59, %60, %61, %62, %63, %64, %65, %66, %67, %68, %69, %70, %71, %72, %73, %74, %75, %76, %77, %78, %79, %80, %81, %82, %83, %84, %85, %86, %87, %88, %89, %90, %91, %92, %93, %94, %95}, "
        "{%96, %97, %98, %99}, db, p, 1, 1, 1;\n}\n"
        : "+f"(d[0]), "+f"(d[1]), "+f"(d[2]), "+f"(d[3]), "+f"(d[4]), "+f"(d[5]), "+f"(d[6]), "+f"(d[7]), "+f"(d[8]), "+f"(d[9]), "+f"(d[10]), "+f"(d[11]), "+f"(d[12]), "+f"(d[13]), "+f"(d[14]), "+f"(d[15]), "+f"(d[16]), "+f"(d[17]), "+f"(d[18]), "+f"(d[19]), "+f"(d[20]), "+f"(d[21]), "+f"(d[22]), "+f"(d[23]), "+f"(d[24]), "+f"(d[25]), "+f"(d[26]), "+f"(d[27]), "+f"(d[28]), "+f"(d[29]), "+f"(d[30]), "+f"(d[31]), "+f"(d[32]), "+f"(d[33]), "+f"(d[34]), "+f"(d[35]), "+f"(d[36]), "+f"(d[37]), "+f"(d[38]), "+f"(d[39]), "+f"(d[40]), "+f"(d[41]), "+f"(d[42]), "+f"(d[43]), "+f"(d[44]), "+f"(d[45]), "+f"(d[46]), "+f"(d[47]), "+f"(d[48]), "+f"(d[49]), "+f"(d[50]), "+f"(d[51]), "+f"(d[52]), "+f"(d[53]), "+f"(d[54]), "+f"(d[55]), "+f"(d[56]), "+f"(d[57]), "+f"(d[58]), "+f"(d[59]), "+f"(d[60]), "+f"(d[61]), "+f"(d[62]), "+f"(d[63]), "+f"(d[64]), "+f"(d[65]), "+f"(d[66]), "+f"(d[67]), "+f"(d[68]), "+f"(d[69]), "+f"(d[70]), "+f"(d[71]), "+f"(d[72]), "+f"(d[73]), "+f"(d[74]), "+f"(d[75]), "+f"(d[76]), "+f"(d[77]), "+f"(d[78]), "+f"(d[79]), "+f"(d[80]), "+f"(d[81]), "+f"(d[82]), "+f"(d[83]), "+f"(d[84]), "+f"(d[85]), "+f"(d[86]), "+f"(d[87]), "+f"(d[88]), "+f"(d[89]), "+f"(d[90]), "+f"(d[91]), "+f"(d[92]), "+f"(d[93]), "+f"(d[94]), "+f"(d[95])
        : "r"(a0), "r"(a1), "r"(a2), "r"(a3), "r"(blo), "r"(scale_d));
}
DEVI void wgmma_rs_n48(float (&d)[120], uint32_t a0, uint32_t a1, uint32_t a2, uint32_t a3, uint32_t blo, uint32_t scale_d) {
    asm volatile("{\n.reg .b64 db;\n.reg .pred p;\n"
        "setp.ne.b32 p, %29, 0;\n"
        "mov.b64 db, {%28, 0xc0000010};\n"
        "wgmma.mma_async.sync.aligned.m64n48k16.f32.bf16.bf16 "
        "{%0, %1, %2, %3, %4, %5, %6, %7, %8, %9, %10, %11, %12, %13, %14, %15, %16, %17, %18, %19, %20, %21, %22, %23}, "
        "{%24, %25, %26, %27}, db, p, 1, 1, 1;\n}\n"
        : "+f"(d[96]), "+f"(d[97]), "+f"(d[98]), "+f"(d[99]), "+f"(d[100]), "+f"(d[101]), "+f"(d[102]), "+f"(d[103]), "+f"(d[104]), "+f"(d[105]), "+f"(d[106]), "+f"(d[107]), "+f"(d[108]), "+f"(d[109]), "+f"(d[110]), "+f"(d[111]), "+f"(d[112]), "+f"(d[113]), "+f"(d[114]), "+f"(d[115]), "+f"(d[116]), "+f"(d[117]), "+f"(d[118]), "+f"(d[119])
        : "r"(a0), "r"(a1), "r"(a2), "r"(a3), "r"(blo), "r"(scale_d));
}
DEVI void wgmma_rs_n192x(float (&d)[120], uint32_t a0, uint32_t a1, uint32_t a2, uint32_t a3, uint32_t blo) {
    asm volatile("{\n.reg .b64 db;\n.reg .pred p;\n"
        "mov.b64 db, {%100, 0x40000000};\n"
        "wgmma.mma_async.sync.aligned.m64n192k16.f32.bf16.bf16 "
        "{%0, %1, %2, %3, %4, %5, %6, %7, %8, %9, %10, %11, %12, %13, %14, %15, %16, %17, %18, %19, %20, %21, %22, %23, %24, %25, %26, %27, %28, %29, %30, %31, %32, %33, %34, %35, %36, %37, %38, %39, %40, %41, %42, %43, %44, %45, %46, %47, %48, %49, %50, %51, %52, %53, %54, %55, %56, %57, %58, %59, %60, %61, %62, %63, %64, %65, %66, %67, %68, %69, %70, %71, %72, %73, %74, %75, %76, %77, %78, %79, %80, %81, %82, %83, %84, %85, %86, %87, %88, %89, %90, %91, %92, %93, %94, %95}, "
        "{%96, %97, %98, %99}, db, 1, 1, 1, 1;\n}\n"
        : "+f"(d[0]), "+f"(d[1]), "+f"(d[2]), "+f"(d[3]), "+f"(d[4]), "+f"(d[5]), "+f"(d[6]), "+f"(d[7]), "+f"(d[8]), "+f"(d[9]), "+f"(d[10]), "+f"(d[11]), "+f"(d[12]), "+f"(d[13]), "+f"(d[14]), "+f"(d[15]), "+f"(d[16]), "+f"(d[17]), "+f"(d[18]), "+f"(d[19]), "+f"(d[20]), "+f"(d[21]), "+f"(d[22]), "+f"(d[23]), "+f"(d[24]), "+f"(d[25]), "+f"(d[26]), "+f"(d[27]), "+f"(d[28]), "+f"(d[29]), "+f"(d[30]), "+f"(d[31]), "+f"(d[32]), "+f"(d[33]), "+f"(d[34]), "+f"(d[35]), "+f"(d[36]), "+f"(d[37]), "+f"(d[38]), "+f"(d[39]), "+f"(d[40]), "+f"(d[41]), "+f"(d[42]), "+f"(d[43]), "+f"(d[44]), "+f"(d[45]), "+f"(d[46]), "+f"(d[47]), "+f"(d[48]), "+f"(d[49]), "+f"(d[50]), "+f"(d[51]), "+f"(d[52]), "+f"(d[53]), "+f"(d[54]), "+f"(d[55]), "+f"(d[56]), "+f"(d[57]), "+f"(d[58]), "+f"(d[59]), "+f"(d[60]), "+f"(d[61]), "+f"(d[62]), "+f"(d[63]), "+f"(d[64]), "+f"(d[65]), "+f"(d[66]), "+f"(d[67]), "+f"(d[68]), "+f"(d[69]), "+f"(d[70]), "+f"(d[71]), "+f"(d[72]), "+f"(d[73]), "+f"(d[74]), "+f"(d[75]), "+f"(d[76]), "+f"(d[77]), "+f"(d[78]), "+f"(d[79]), "+f"(d[80]), "+f"(d[81]), "+f"(d[82]), "+f"(d[83]), "+f"(d[84]), "+f"(d[85]), "+f"(d[86]), "+f"(d[87]), "+f"(d[88]), "+f"(d[89]), "+f"(d[90]), "+f"(d[91]), "+f"(d[92]), "+f"(d[93]), "+f"(d[94]), "+f"(d[95])
        : "r"(a0), "r"(a1), "r"(a2), "r"(a3), "r"(blo));
}
DEVI void wgmma_rs_n48x(float (&d)[120], uint32_t a0, uint32_t a1, uint32_t a2, uint32_t a3, uint32_t blo) {
    asm volatile("{\n.reg .b64 db;\n.reg .pred p;\n"
        "mov.b64 db, {%28, 0xc0000000};\n"
        "wgmma.mma_async.sync.aligned.m64n48k16.f32.bf16.bf16 "
        "{%0, %1, %2, %3, %4, %5, %6, %7, %8, %9, %10, %11, %12, %13, %14, %15, %16, %17, %18, %19, %20, %21, %22, %23}, "
        "{%24, %25, %26, %27}, db, 1, 1, 1, 1;\n}\n"
        : "+f"(d[96]), "+f"(d[97]), "+f"(d[98]), "+f"(d[99]), "+f"(d[100]), "+f"(d[101]), "+f"(d[102]), "+f"(d[103]), "+f"(d[104]), "+f"(d[105]), "+f"(d[106]), "+f"(d[107]), "+f"(d[108]), "+f"(d[109]), "+f"(d[110]), "+f"(d[111]), "+f"(d[112]), "+f"(d[113]), "+f"(d[114]), "+f"(d[115]), "+f"(d[116]), "+f"(d[117]), "+f"(d[118]), "+f"(d[119])
        : "r"(a0), "r"(a1), "r"(a2), "r"(a3), "r"(blo));
}
DEVI void wgmma_rs_n80(float (&d)[40], uint32_t a0, uint32_t a1, uint32_t a2, uint32_t a3, uint32_t blo, uint32_t scale_d) {
    asm volatile("{\n.reg .b64 db;\n.reg .pred p;\n"
        "setp.ne.b32 p, %45, 0;\n"
        "mov.b64 db, {%44, 0x40000040};\n"
        "wgmma.mma_async.sync.aligned.m64n80k16.f32.bf16.bf16 "
        "{%0, %1, %2, %3, %4, %5, %6, %7, %8, %9, %10, %11, %12, %13, %14, %15, %16, %17, %18, %19, %20, %21, %22, %23, %24, %25, %26, %27, %28, %29, %30, %31, %32, %33, %34, %35, %36, %37, %38, %39}, "
        "{%40, %41, %42, %43}, db, p, 1, 1, 1;\n}\n"
        : "+f"(d[0]), "+f"(d[1]), "+f"(d[2]), "+f"(d[3]), "+f"(d[4]), "+f"(d[5]), "+f"(d[6]), "+f"(d[7]), "+f"(d[8]), "+f"(d[9]), "+f"(d[10]), "+f"(d[11]), "+f"(d[12]), "+f"(d[13]), "+f"(d[14]), "+f"(d[15]), "+f"(d[16]), "+f"(d[17]), "+f"(d[18]), "+f"(d[19]), "+f"(d[20]), "+f"(d[21]), "+f"(d[22]), "+f"(d[23]), "+f"(d[24]), "+f"(d[25]), "+f"(d[26]), "+f"(d[27]), "+f"(d[28]), "+f"(d[29]), "+f"(d[30]), "+f"(d[31]), "+f"(d[32]), "+f"(d[33]), "+f"(d[34]), "+f"(d[35]), "+f"(d[36]), "+f"(d[37]), "+f"(d[38]), "+f"(d[39])
        : "r"(a0), "r"(a1), "r"(a2), "r"(a3), "r"(blo), "r"(scale_d));
}
DEVI void wgmma_ss_n80(float (&d)[40], uint32_t alo, uint32_t blo) {
    asm volatile("{\n.reg .b64 da, db;\n"
        "mov.b64 da, {%40, 0x10};\n"
        "mov.b64 db, {%41, 0x40000040};\n"
        "wgmma.mma_async.sync.aligned.m64n80k16.f32.bf16.bf16 "
        "{%0, %1, %2, %3, %4, %5, %6, %7, %8, %9, %10, %11, %12, %13, %14, %15, %16, %17, %18, %19, %20, %21, %22, %23, %24, %25, %26, %27, %28, %29, %30, %31, %32, %33, %34, %35, %36, %37, %38, %39}, "
        "da, db, 1, 1, 1, 0, 1;\n}\n"
        : "+f"(d[0]), "+f"(d[1]), "+f"(d[2]), "+f"(d[3]), "+f"(d[4]), "+f"(d[5]), "+f"(d[6]), "+f"(d[7]), "+f"(d[8]), "+f"(d[9]), "+f"(d[10]), "+f"(d[11]), "+f"(d[12]), "+f"(d[13]), "+f"(d[14]), "+f"(d[15]), "+f"(d[16]), "+f"(d[17]), "+f"(d[18]), "+f"(d[19]), "+f"(d[20]), "+f"(d[21]), "+f"(d[22]), "+f"(d[23]), "+f"(d[24]), "+f"(d[25]), "+f"(d[26]), "+f"(d[27]), "+f"(d[28]), "+f"(d[29]), "+f"(d[30]), "+f"(d[31]), "+f"(d[32]), "+f"(d[33]), "+f"(d[34]), "+f"(d[35]), "+f"(d[36]), "+f"(d[37]), "+f"(d[38]), "+f"(d[39])
        : "r"(alo), "r"(blo));
}

#define SVC_D 0
#define SVC_NS 60
DEVI unsigned redux_max(unsigned v) { return __reduce_max_sync(0xffffffffu, v); }

DEVI void service_cta(Scratch* __restrict__ sc, const __nv_bfloat16* __restrict__ x, const __nv_bfloat16* __restrict__ wr, uint32_t sb, int h, int tid, uint32_t t_start) {
    const int warp = tid >> 5, lane = tid & 31;
    Outbox* const box = &sc->box[h];
    const unsigned tag = ld_relaxed_u32(&sc->epoch[(NCTA + h) * 32]) + 1;
    if (tid < 256) st_relaxed_v4(&box->msg[0] + tid, make_uint4(EMPTY_WORD, EMPTY_WORD, EMPTY_WORD, EMPTY_WORD));
    __syncthreads();
    unsigned spins = 0;
    if (warp == 0) {
        fence_gpu();
        if (lane < 2) st_relaxed_v4(&sc->open[h][lane * 4], make_uint4(tag, tag, tag, tag));
    }
    if (warp >= 8) {
        const int t = tid - 256;
        float wsum = 0.f;
        __nanosleep(1000);
#pragma unroll
        for (int j = 0; j < 10; j++) { const uint32_t v = reinterpret_cast<const uint32_t*>(wr)[lane + 32 * j]; wsum += bf_lo(v) + bf_hi(v); }
#pragma unroll
        for (int o = 1; o < 32; o <<= 1) wsum += shfl_x(wsum, o);
        uint4 q[4];
        const uint4* src = reinterpret_cast<const uint4*>(&sc->rowinfo[0][0][0]) + t;
#pragma unroll
        for (int j = 0; j < 4; j++) q[j].y = q[j].w = tag - 1;
        while (true) {
            unsigned bad = 0;
#pragma unroll
            for (int j = 0; j < 4; j++) if (((q[j].y ^ tag) | (q[j].w ^ tag)) & 15) q[j] = ld_relaxed_v4(src + 256 * j);
            __syncwarp();
#pragma unroll
            for (int j = 0; j < 4; j++) bad |= (q[j].y ^ tag) | (q[j].w ^ tag);
            if (__all_sync(0xffffffffu, (bad & 15) == 0)) break;
            if (spins == 0) while (!__any_sync(0xffffffffu, ((ld_relaxed_v4(src).y ^ tag) & 15) == 0)) { __nanosleep(100); spin_guard(spins); }
            spin_guard(spins);
        }
        if (t == 0) TL(2);
        unsigned a = 0, b = 0;
#pragma unroll
        for (int j = 0; j < 8; j++) {
            const uint32_t info = (j & 1) ? q[j >> 1].z : q[j >> 1].x;
            const uint32_t u = pack_bf16(fmaf(-bf_lo(info), wsum, __uint_as_float((j & 1) ? q[j >> 1].w : q[j >> 1].y)) * rcp(bf_hi(info)), 0.f);
            const int row = ((j >> 1) * 4 + (t >> 6)) * 128 + 4 * (t & 31) + 2 * (j & 1) + ((t >> 5) & 1);
            const unsigned key = (((u & 0x8000u) ? (u ^ 0xffffu) : (u | 0x8000u)) << 16) | ((2047 - row) << 5);
            b = max(b, min(a, key)); a = max(a, key);
        }
        unsigned k1 = redux_max(a), k2 = redux_max(a == k1 ? b : a);
        if (lane == 0) sts_f2(sb + 8192 + (warp - 8) * 8, __uint_as_float(k1), __uint_as_float(k2));
        bar_sync<2, 256>();
        if (t == 0) TL(0);
        a = lds_u32(sb + 8192 + (lane & 15) * 4);
        k1 = redux_max(a); k2 = redux_max(a == k1 ? 0u : a);
        if (t < 160) {
            const int tk = t >= 80, sel = 2047 - (((tk ? k2 : k1) >> 5) & 2047);
            const uint4 xq = ldg_v4(reinterpret_cast<const uint4*>(x + sel * DM) + t - tk * 80);
            const unsigned info = ld_relaxed_u32(&sc->rowinfo[sel >> 7][sel & 1][(sel & 127) >> 1]);
            const uint32_t mm = __byte_perm(info, 0, 0x1010);
            const float rs = rcp(bf_hi(info));
            uint32_t o[4];
#pragma unroll
            for (int e = 0; e < 4; e++) { const uint32_t d = hsub2((&xq.x)[e], mm); o[e] = pack_bf16(bf_lo(d) * rs, bf_hi(d) * rs); }
            st_relaxed_v4(&box->msg[t + tk], make_uint4(o[0], o[1], o[2], o[3]));
            sts_v4(sb + SM_XSEL + (t + tk) * 16, make_uint4(o[0], o[1], o[2], o[3]));
        } else if (t == 160) {
            const uint4 top = make_uint4(2047 - ((k1 >> 5) & 2047), 2047 - ((k2 >> 5) & 2047), k1, k2);
            st_relaxed_v4(&box->msg[80], top); sts_v4(sb + SM_TOP, top); TL(1);
        }
        if (t == 0) TL(3);
    }
    __syncthreads();
    const uint4* src = &sc->yp[2 * h + (warp >> 3)][warp & 7][0];
    const int nj = (warp & 7) < 6 ? 7 : 6;
    uint4 v[7];
#pragma unroll
    for (int j = 0; j < 7; j++) v[j] = make_uint4(0, 0, 0, j < nj ? tag - 1 : tag & 255);
    while (NMOE) {
        unsigned miss = 0;
#pragma unroll
        for (int j = 0; j < 7; j++) miss |= ((v[j].w ^ tag) & 255) ? 1u << j : 0u;
        miss = __reduce_or_sync(0xffffffffu, miss);
        if (!miss) break;
        if (__popc(miss) > SVC_D) {
            miss &= __ballot_sync(0xffffffffu, ((ld_relaxed_u32(&src[min(lane & 7, nj - 1) * 256 + 31].w) ^ tag) & 255) == 0);
            if (!miss) __nanosleep(SVC_NS);
        }
#pragma unroll
        for (int j = 0; j < 7; j++) if ((miss >> j) & 1) v[j] = ld_relaxed_v4(src + j * 256 + lane);
        spin_guard(spins);
    }
    if (tid == 0) TL(4);
    float y[5] = {0.f, 0.f, 0.f, 0.f, 0.f};
#pragma unroll
    for (int j = 0; j < 7; j++) {
        y[0] += __uint_as_float(v[j].x & ~255u); y[1] += __uint_as_float(v[j].y & ~255u); y[2] += __uint_as_float(v[j].z & ~255u); y[3] += __uint_as_float(v[j].w & ~255u);
        y[4] += __uint_as_float(__byte_perm(__byte_perm(v[j].x, v[j].y, 0x0400), v[j].z, 0x4210) & ~255u);
    }
#pragma unroll
    for (int e = 0; e < 5; e++) sts_u32(sb + (warp * 160 + e * 32 + lane) * 4, __float_as_uint(y[e]));
    __syncthreads();
    if (tid == 0) TL(6);
    if (warp < 10) {
        const int gi = warp >= 5, e = warp - 5 * gi, tk = lane & 1, col = e * 16 + (lane >> 2) + 4 * (lane & 2);
        float sum = 0.f;
#pragma unroll
        for (int j = 0; j < 8; j++) sum += lds_f32(sb + ((gi * 8 + j) * 160 + e * 32 + lane) * 4);
        const uint32_t ks = lds_u32(sb + SM_TOP + 8 + tk * 4) >> 16;
        const float sg = bfr(sigmoid_f(__uint_as_float(((ks & 0x8000u) ? (ks & 0x7fffu) : (ks ^ 0xffffu)) << 16)));
        sts_u16(sb + 16384 + gi * 512 + tk * 160 + col * 2,
                pack_bf16(silu_f(bfr(bf_lo(lds_u16(sb + SM_XSEL + tk * 1296 + ((2 * h + gi) * 80 + col) * 2)) + bfr(bfr(sum) * sg))), 0.f));
        bar_sync<1, 320>();
        if (warp < 2 && lane < 20) st_relaxed_v4(&box->gt[warp][lane], lds_v4(sb + 16384 + tid * 16));
    }
    if (tid == 0) { st_relaxed_u32(&sc->epoch[(NCTA + h) * 32], tag); TL(5); }
}

template <int ODD, int HALF> DEVI void pack_kv(const float (&acc)[120], uint32_t (&K)[10][2], uint32_t (&V)[10][2]) {
#pragma unroll
    for (int b = 0; b < 10; b++) {
        const int pb = ODD ? (b + 8) % 10 : b, jk = pb < 8 ? 8 + pb : 18 + pb, jv = pb < 8 ? 16 + pb : 20 + pb;
        V[b][HALF] = movm(pack_bf16(acc[4 * jv + 2 * HALF], acc[4 * jv + 2 * HALF + 1]));
        K[b][HALF] = pack_bf16(acc[4 * jk + 2 * HALF], acc[4 * jk + 2 * HALF + 1]);
    }
}
template <int ODD> DEVI void pack_q(const float (&acc)[120], uint32_t (&Q)[10][2]) {
#pragma unroll
    for (int b = 0; b < 10; b++) {
        const int pb = ODD ? (b + 8) % 10 : b, jq = pb < 8 ? pb : 16 + pb;
        Q[b][0] = pack_bf16(acc[4 * jq], acc[4 * jq + 1]); Q[b][1] = pack_bf16(acc[4 * jq + 2], acc[4 * jq + 3]);
    }
}

#define KROT 5
#define WOP 8
#define SIDE_N -1
#define PIPE_POLL 0
#define NSIDE 4
#define WO_S 6
#define TAIL_NS 50
#define WO_GATE 4
#define MSG_NS 800
#define T2_NS 0
#define JL 6
#define G7T 10
#define PRE_D 1
#define POLL2 0
#define POLL2_GAP 60
#define G1S 0
#define XJ 2
#define FXN 4
#define SWAP 0
#define MSGW 8
#define TAILM 0
#define WTT 10
#define MSG_POLL 100
#define DPN 4
#define GDELAY 0
#define G2DELAY 400
#define NCHK 3
#define ANP 0
#define WO_L 8
#define G1DELAY 150
#define RS_H -1
#define RS_NS 0
#define NPRE 12
#define GT_NS 0
#define MSG_KT 12
#define F2W 1
#define RS_L 3
#define GI_T 0
#define SPLIT 3
#define RS_PACE(t) (t + JL - 5)
#define ATS(i)
#define G1_DONE() do { if ((tid & 127) == 32) mbar_arrive(bars + BAR_GI * 8); } while (0)
#define SRC(i) ((i) == 0 ? g : ((i) - 1 < g ? (i) - 1 : (i)))

DEVI void gather_o(const Scratch* sc, uint32_t sb, int m, int g, int lane, int slot
                   ) {
    const uint32_t bars = sb + SM_BAR;
    uint32_t tb = bars + (BAR_TB + slot) * 8;
    const uint32_t dst = sb + (slot == 0 ? SM_O0 : (slot == 1 ? SM_O1 : SM_O2)), n1 = g * 4096;
    unsigned ph = 0;
#pragma unroll
    for (int t = slot; t < 5; t += 3) {
        const uint4* os = &sc->o[m][t][0][0];
        if (t >= NCHK) tb = bars + (BAR_OF + t) * 8;
        if (elect_one()) mbar_expect_tx(tb, 28672);
        if (t) {
            mbar_wait(bars + (BAR_OE + t - 1) * 8, 0);
            if (t < 3) { mbar_spin(bars + (BAR_PA + t) * 8, 0); mbar_spin(bars + BAR_GO * 8, 0); if (t == 2 && G2DELAY) __nanosleep(G2DELAY); if (t == 1 && G1DELAY) __nanosleep(G1DELAY); }
        } else {
            const unsigned* fl = &sc->flag[m * 8 + ((lane & 7) == g ? g ^ 1 : lane & 7)][1];
            const unsigned tag = lds_u32(sb + SM_TAG);
            asm volatile("" : "+l"(fl));
            mbar_spin(bars + BAR_AN * 8, 0);
            if (lane == 0) { st_relaxed_u32(const_cast<unsigned*>(&sc->flag[m * 8 + g][1]), tag); TL(53); }
            unsigned spins = 0;
            while (__any_sync(0xffffffffu, ld_relaxed_u32(fl) != tag)) spin_guard(spins);
            if (GDELAY) __nanosleep(GDELAY);
        }
        if (elect_one()) {
            if (g > 0) bulk_load(dst, os, n1, tb);
            if (g < 7) bulk_load(dst + n1, os + (g + 1) * 256, 28672 - n1, tb);
            if (t == 0) mbar_arrive(bars + BAR_GO * 8);
            TL(48 + t);
        }
        __syncwarp();
        if (t >= NCHK) continue;
        while (true) {
            mbar_spin(tb, ph++ & 1);
            if (t == 0 && lane == 0) TL(47);
            unsigned v[7], miss = 0;
#pragma unroll
            for (int i = 0; i < 7; i++) v[i] = lds_u32(dst + i * 4096 + lane * 132);
            if (!__any_sync(0xffffffffu, max(max(max(v[0], v[1]), max(v[2], v[3])), max(max(v[4], v[5]), v[6])) == EMPTY_WORD) || ph > SPIN_MAX) break;
#pragma unroll
            for (int i = 0; i < 7; i++) miss |= v[i] == EMPTY_WORD ? 1u << i : 0u;
            miss = __reduce_or_sync(0xffffffffu, miss);
            if (elect_one()) {
                mbar_expect_tx(tb, __popc(miss) * 4096);
#pragma unroll 1
                for (int i = 0; i < 7; i++) if ((miss >> i) & 1) bulk_load(dst + i * 4096, os + (i + (i >= g)) * 256, 4096, tb);
            }
            __syncwarp();
        }
        if (lane == 0) mbar_arrive(bars + (BAR_OF + t) * 8);
    }
}
#define GATHER(slot) gather_o(sc, sb, m, g, lane, slot)

__global__ void __cluster_dims__(2, 1, 1) __launch_bounds__(NTHREADS, 1) fused_kernel(
    Scratch* __restrict__ sc,
    const __nv_bfloat16* __restrict__ x, const __nv_bfloat16* __restrict__ wqkv, const __nv_bfloat16* __restrict__ wo, const __nv_bfloat16* __restrict__ wr,
    const __nv_bfloat16* __restrict__ wd, __nv_bfloat16* __restrict__ out, const int by_sm, const __grid_constant__ Roles roles,
    const __grid_constant__ CUtensorMap tm_x, const __grid_constant__ CUtensorMap tm_w, const __grid_constant__ CUtensorMap tm_wt,
    const __grid_constant__ CUtensorMap tm_wo, const __grid_constant__ CUtensorMap tm_wn, const __grid_constant__ CUtensorMap tm_d,
    const __grid_constant__ CUtensorMap tm_g, const __grid_constant__ CUtensorMap tm_u, const __grid_constant__ CUtensorMap tm_o)
{
    extern __shared__ __align__(1024) unsigned char smem[];
    const uint32_t t_start = 0;
    const uint32_t bid = blockIdx.x, tid = threadIdx.x;
    uint32_t sb, smid;
    asm volatile("mov.u32 %0, %1;" : "=r"(sb) : "r"(smem_u32(smem)));
    asm volatile("mov.u32 %0, %%smid;" : "=r"(smid));
    const unsigned cta = roles.pair[(by_sm ? smid : bid) >> 1] * 2 + (bid & 1);
    const int warp = __shfl_sync(0xffffffffu, tid >> 5, 0), lane = tid & 31;
    const uint32_t bars = sb + SM_BAR;
#define BAR_COUNT(s) ((s >> 2) == 1 ? 4 : (s >= BAR_AE ? (s >= BAR_FA ? (s == BAR_AN ? 9 : 1) : (s == BAR_AE + 5 ? 2 : 4)) : (s >= BAR_PA ? 8 : (s == BAR_CS || s == BAR_OE + 1 ? 4 : s == BAR_OE && NPRE == 12 ? 5 : (s >= BAR_OE + 2 || s == BAR_GI ? 2 : 1)))))
#define INIT_BARS(a, b) do { if (elect_one()) { _Pragma("unroll") for (int s = a; s < b; s++) if (s != BAR_FA || (a) == BAR_FA) mbar_init(bars + s * 8, BAR_COUNT(s)); \
        asm volatile("fence.mbarrier_init.release.cluster;" ::: "memory"); } __syncwarp(); } while (0)
    if (warp >= 8) {
        if (warp == 8) INIT_BARS(BAR_FA, BAR_FA + 1);
        else if (warp == 9) INIT_BARS(0, 23);
        else if (warp == 10) INIT_BARS(23, NBAR);
    }
    cluster_arrive();
    if (warp < 2) {
        const uint32_t i = tid - 32;
        if (tid < 30 && bid < NCTA) asm volatile("prefetch.global.L2 [%0];" :: "l"(reinterpret_cast<const char*>(wqkv) + (bid * 15 + tid + (tid >= 15 ? KROT * 1920 - 15 : 0)) * 128) : "memory");
        if (i < 16) asm volatile("prefetch.global.L2 [%0];" :: "l"(bid < NCTA ? reinterpret_cast<const char*>(x) + (bid * 16 + i) * 1280 + (bid & 16) * (KROT * 8)
                                                                             : reinterpret_cast<const char*>(wr) + min(i, 9u) * 128) : "memory");
    }
    if (cta >= NCTA) { cluster_wait(); service_cta(sc, x, wr, sb, cta - NCTA, tid, t_start); return; }
    const int rank = cta & 1, g = (cta >> 1) & 7, G = cta >> 4, m = 2 * G + rank, odd = g & 1;
    const int k0 = (G & 1) * KROT * 64;
    const int cm = g * 80 + odd * 16, ct = g * 80 + 64 - odd * 64;

#define NP0 2
#define TILE_X(kt, kk) tma3d(sb + (-(kt) & 3) * STAGE, &tm_x, bars + (BAR_FA + ((kt) & 3)) * 8, kk, m * 64, 0)
#define TILE_W(kt, kk) do { const uint32_t fb_ = bars + (BAR_FULL + ((kt) & 3)) * 8, st_ = sb + (-(kt) & 3) * STAGE + OFF_B; \
        tma3d_mc(st_ + rank * B_HALF, &tm_w, fb_, cm, (kk) + rank * 32, 0); \
        tma3d(st_ + 12288, &tm_wt, fb_, ct, kk, 0); tma3d(st_ + B_HALF + 12288, &tm_wt, fb_, ct, (kk) + 32, 0); } while (0)
    if (warp == 8) {
        if (elect_one()) { mbar_expect_tx(bars + BAR_FA * 8, OFF_B); TILE_X(0, k0); }
        cluster_wait();
        if (elect_one()) {
            mbar_expect_tx(bars + BAR_FULL * 8, 2 * B_HALF);
            TILE_W(0, k0);
            mbar_expect_tx(bars + BAR_WR * 8, 1280); bulk_load(sb + SM_XSEL, wr, 1280, bars + BAR_WR * 8);
            TL(16);
#pragma unroll
            for (int kt = 1; kt < NP0; kt++) {
                mbar_expect_tx(bars + (BAR_FA + kt) * 8, OFF_B); mbar_expect_tx(bars + (BAR_FULL + kt) * 8, 2 * B_HALF);
                TILE_X(kt, k0 + kt * 64); TILE_W(kt, k0 + kt * 64);
                if (kt == 1) TL(29);
            }
        }
        __syncwarp();
    }
    if (warp >= 8) {
        asm volatile("setmaxnreg.dec.sync.aligned.u32 72;");
        const int mi = g < 6 ? G * 6 + g : 46 + G;
        const bool moe = g < 6 || (g == 6 && G >= 2);
        const Outbox* const box = &sc->box[g >> 1];
#define FETCH_MSG() do { \
                while (ld_relaxed_u32(&box->msg[80]) == EMPTY_WORD) { __nanosleep(MSG_POLL); spin_guard(spins); } \
                if (lane == 0) TL(61); \
                uint4 q[6]; \
                while (true) { \
                    _Pragma("unroll") for (int j = 0; j < 6; j++) q[j] = ld_relaxed_v4(&box->msg[min(lane + 32 * j, 160)]); \
                    __syncwarp(); \
                    if (__all_sync(0xffffffffu, max(max(max(q[0].x, q[1].x), max(q[2].x, q[3].x)), max(q[4].x, q[5].x)) != EMPTY_WORD)) break; \
                    spin_guard(spins); \
                } \
                _Pragma("unroll") for (int j = 0; j < 6; j++) sts_v4(sb + SM_XSEL + min(lane + 32 * j, 160) * 16, q[j]); \
                __syncwarp(); \
                if (lane == 0) { mbar_arrive(bars + BAR_SEL * 8); TL(23); } } while (0)
        if (warp == 8) {
            const CUtensorMap* tm_gu = rank ? &tm_u : &tm_g;
            if (elect_one()) { mbar_expect_tx(bars + BAR_WO * 8, WO_L * 10240); mbar_expect_tx(bars + BAR_W2 * 8, (8 - WO_L) * 10240); mbar_expect_tx(bars + BAR_GW * 8, 40960); mbar_expect_tx(bars + BAR_DW * 8, 20480); }
#pragma unroll 1
            for (int kt = NP0; kt < 13; kt++) {
                if (kt >= 4) { if (kt < 4 + JL) mbar_wait(bars + (BAR_AE + kt - 4) * 8, 0); mbar_wait(bars + (BAR_EMPTY + (kt & 3)) * 8, ((kt >> 2) - 1) & 1); }
                if (elect_one()) {
                    if (kt < 10) {
                        const int kk = kt * 64 + (kt < 5 ? k0 : -k0);
                        mbar_expect_tx(bars + (BAR_FA + (kt & 3)) * 8, OFF_B); mbar_expect_tx(bars + (BAR_FULL + (kt & 3)) * 8, 2 * B_HALF);
                        TILE_X(kt, kk); TILE_W(kt, kk);
                        if (kt == WOP) prefetch_l2_bulk(reinterpret_cast<const char*>(wo) + cta * 6400, 6400);
                    }
                    if (moe) {
                        if ((unsigned)(kt - GP0) < 7u) tma2d(sb + SM_MW + (kt - GP0) * 5120, tm_gu, bars + BAR_GW * 8, mi * 32, (kt - GP0) * 80);
                        if (kt == G7T) tma2d(sb + SM_G7, tm_gu, bars + BAR_GW * 8, mi * 32, 560);
                        if ((unsigned)(kt - DP0) < (unsigned)DPN) prefetch_l2_bulk(wd + (mi * 32 + rank * 16 + (kt - DP0) * (16 / DPN)) * DM, 20480 / DPN);
                        if (kt == 12) {
#pragma unroll
                            for (int i = 0; i < 5; i++) tma2d(sb + SM_DW + i * 4096, &tm_d, bars + BAR_DW * 8, (rank * 5 + i) * 64, mi * 32);
                        }
                    }
                    if (kt == 3) TL(17);
                }
                __syncwarp();
                if (MSGW == 8 && kt == MSG_KT) { unsigned spins = 0; mbar_wait(bars + BAR_RS * 8, 0); FETCH_MSG(); }
                if (kt >= 10) {
                    if (kt == 11 && (WO_GATE & 2)) mbar_wait(bars + BAR_RS * 8, 0);
                    if (kt == 11 && (WO_GATE & 1)) mbar_wait(bars + BAR_CS * 8, 0);
                    if (kt == 12 && (WO_GATE & 4)) mbar_wait(bars + BAR_SEL * 8, 0);
                    if (elect_one()) {
                        if (TAILM && kt == WTT) { mbar_expect_tx(bars + BAR_WT * 8, 20480); tma3d(sb + SM_WT, &tm_wn, bars + BAR_WT * 8, ct, 0, 0); }
#pragma unroll
                        for (int i0 = (kt == 10 ? 0 : (kt == 11 ? 2 : WO_S)); i0 < (kt == 10 ? 2 : (kt == 11 ? WO_S : WO_L)); i0 += 2) {
                            const int i = i0 + rank;
                            tma2d_mc(sb + SM_WO + (7 - i) * 10240, &tm_wo, bars + BAR_WO * 8, cm, SRC(i) * 80);
                        }
                    }
                    __syncwarp();
                }
            }
            mbar_wait(bars + BAR_GI * 8, 0);
            if (lane == 0) mbar_arrive_at(bars + BAR_PG * 8, rank ^ 1);
            mbar_wait(bars + BAR_PG * 8, 0);
            GATHER(0);
        } else {
            const int ta = tid - 288, wa = (SWAP && warp >= 12 ? warp ^ 2 : warp) - 9, c = lane & 3, r = lane >> 2;
            const unsigned tag = ld_relaxed_u32(&sc->epoch[cta * 32]) + 1;
            unsigned spins = 0;
            if (wa == 0) {
                const uint4 e = make_uint4(EMPTY_WORD, EMPTY_WORD, EMPTY_WORD, EMPTY_WORD);
                uint4* ro = &sc->o[m][0][g][lane];
                cluster_wait();
                if (lane == 0) { mbar_expect_tx(bars + BAR_PX * 8, 2560); sts_u32(sb + SM_TAG, tag); }
                if (RS_H >= 0) mbar_wait(bars + (BAR_AE + RS_H) * 8, 0);
                if (RS_H == -1) mbar_wait(bars + BAR_WR * 8, 0);
#pragma unroll
                for (int i = 0; i < 10; i++) st_relaxed_v4(&sc->halo[m * 8 + g][lane + 32 * i], e);
                fence_gpu();
                __syncwarp();
                if (lane < 2) st_relaxed_v4(&sc->flag[m * 8 + g][lane * 4], make_uint4(tag, 0, 0, 0));
                if (lane == 0) TL(58);
#pragma unroll 1
                for (int t = 0; t < 5; t++, ro += 2048) {
                    if (t >= RS_L) mbar_wait(bars + BAR_CS * 8, 0);
                    else if (!RS_NS) mbar_wait(bars + (BAR_AE + RS_PACE(t)) * 8, 0);
#pragma unroll
                    for (int i = 0; i < 8; i++) st_relaxed_v4(ro + 32 * i, e);
                    if (RS_NS) __nanosleep(RS_NS);
                }
                const unsigned* rd = lane == 0 && m > 0 ? &sc->flag[m * 8 + g - 8][0] : &sc->open[g >> 1][0];
                while (!__all_sync(0xffffffffu, ld_relaxed_u32(rd) == tag)) { __nanosleep(POLL_NS); spin_guard(spins); }
                if (lane == 0) { mbar_arrive(bars + BAR_RS * 8); TL(21); }
                if (F2W) mbar_wait(bars + (F2W == 1 ? BAR_CS : BAR_SEL) * 8, 0);
                fence_gpu();
                __syncwarp();
                if (lane == 0) { mbar_arrive(bars + BAR_AN * 8); TL(20); }
                if (MSGW == 0) FETCH_MSG();
                if (WO_L < 8) {
                    mbar_wait(bars + BAR_PG * 8, 0); mbar_spin(bars + BAR_AN * 8, 0);
                    if (elect_one()) {
#pragma unroll
                        for (int i0 = WO_L; i0 < 8; i0 += 2) { const int i = i0 + rank; tma2d_mc(sb + SM_WO + (7 - i) * 10240, &tm_wo, bars + BAR_W2 * 8, cm, SRC(i) * 80); }
                    }
                    __syncwarp();
                }
                GATHER(1);
                return;
            } else {
                const bool cw = wa < 3, aside = wa >= 5;
                const int l = min(lane, 29), part = l < 24 ? l >> 3 : (l - 24) >> 1;
                const int pp = warp & 1, ri = lane >> 3;
                float s[8];
#pragma unroll
                for (int e = 0; e < 8; e++) s[e] = 0.f;
                const uint32_t k16 = roles.k16, khi = 0x3f800000u;
#define U_LO(v) __uint_as_float(imul(v, k16))
#define U_HI(v) __uint_as_float(hfma2(v, khi, 0u))
#define GAPS 1
#define GAP(...) do { if (GAPS) { asm volatile("pmevent 0;" : __VA_ARGS__ :: "memory"); } } while (0)
#define ROW_SUMS(v0, v1, v2) do { _Pragma("unroll") for (int e = 0; e < 4; e++) { \
                    const float wl = U_LO((&v2.x)[e]), wh = U_HI((&v2.x)[e]), a = U_LO((&v0.x)[e]), b = U_HI((&v0.x)[e]); \
                    s[0] += a; s[1] = fmaf(a, a, s[1]); s[2] = fmaf(a, wl, s[2]); s[0] += b; s[1] = fmaf(b, b, s[1]); s[2] = fmaf(b, wh, s[2]); \
                    GAP("+f"(s[0]), "+f"(s[1]), "+f"(s[2]), "+r"((&v1.x)[e])); \
                    const float a2 = U_LO((&v1.x)[e]), b2 = U_HI((&v1.x)[e]); \
                    s[4] += a2; s[5] = fmaf(a2, a2, s[5]); s[6] = fmaf(a2, wl, s[6]); s[4] += b2; s[5] = fmaf(b2, b2, s[5]); s[6] = fmaf(b2, wh, s[6]); \
                    GAP("+f"(s[4]), "+f"(s[5]), "+f"(s[6]), "+r"((&v0.x)[(e + 1) & 3]), "+r"((&v2.x)[(e + 1) & 3])); } } while (0)
                if (aside) {
                    const __nv_bfloat16* p0 = x + (m * 128 + g * 16 + 2 * ri + pp) * DM + 64 * JL - k0 + (lane & 7) * 8;
                    const uint32_t wa2 = sb + SM_XSEL + (lane & 7) * 16 + 128 * JL - 2 * k0;
                    cluster_wait();
                    mbar_wait(bars + BAR_WR * 8, 0);
                    if (SIDE_N >= 0) mbar_wait(bars + (BAR_AE + SIDE_N) * 8, 0);
                    uint4 q[10 - JL][2];
#pragma unroll
                    for (int j = 0; j < 10 - JL; j++) { q[j][0] = ldg_v4(p0 + j * 64); q[j][1] = ldg_v4(p0 + 8 * DM + j * 64); }
                    uint4 wn = lds_v4(wa2);
                    __syncwarp();
#pragma unroll
                    for (int j = 0; j < 10 - JL; j++) { uint4 wv = wn; if (j < 9 - JL) wn = lds_v4(wa2 + (j + 1) * 128); ROW_SUMS(q[j][0], q[j][1], wv); }
                    if (wa == 5 && lane == 0) TL(62);
                } else {
                    uint32_t ad[4];
#pragma unroll
                    for (int i = 0; i < 4; i++) {
                        const int row = 4 * ((G & 6) + pp) + i;
                        ad[i] = cw ? OFF_B + rank * B_HALF + (l < 24 ? part * 4096 + row * 128 + (((l ^ row) & 7) << 4) : 12288 + part * 1024 + row * 32 + (((l ^ pp) & 1) << 4))
                                   : (i < 2 ? pp * 8192 + (8 * g + ri + 4 * i) * 128 + (((lane ^ (ri + 4 * i)) & 7) << 4) : SM_XSEL + (lane & 7) * 16 + 2 * k0);
                        ad[i] = __shfl_sync(0xffffffffu, sb + ad[i], lane);
                    }
                    if (wa == 1) st_relaxed_v4(&sc->cs[g][G][rank][lane], make_uint4(tag - 1, 0, 0, 0));
                    cluster_wait();
                    if (ta == 32) mbar_expect_tx(bars + BAR_CX * 8, 2048);
                    mbar_wait(bars + BAR_WR * 8, 0);
#pragma unroll 1
                    for (int kt = 0; kt < (cw ? 5 : JL); kt++) {
                        const uint32_t so = (-kt & 3) * STAGE;
                        mbar_wait(bars + ((cw ? BAR_FULL : BAR_FA) + (kt & 3)) * 8, kt >> 2);
                        uint4 v0 = lds_v4(ad[0] + so), v1 = lds_v4(ad[1] + so), v2 = lds_v4(ad[2] + (cw ? so : kt * 128 - (kt == 5 ? 4 * k0 : 0)));
                        if (cw) {
                            const uint4 v3 = lds_v4(ad[3] + so);
#pragma unroll
                            for (int e = 0; e < 4; e++) {
                                s[2 * e] += U_LO((&v0.x)[e]); s[2 * e + 1] += U_HI((&v0.x)[e]); s[2 * e] += U_LO((&v1.x)[e]); s[2 * e + 1] += U_HI((&v1.x)[e]);
                                s[2 * e] += U_LO((&v2.x)[e]); s[2 * e + 1] += U_HI((&v2.x)[e]); s[2 * e] += U_LO((&v3.x)[e]); s[2 * e + 1] += U_HI((&v3.x)[e]);
                                GAP("+f"(s[2 * e]), "+f"(s[2 * e + 1]));
                            }
                        } else ROW_SUMS(v0, v1, v2);
                        __syncwarp();
                        if (lane == 0) mbar_arrive(bars + (BAR_AE + kt) * 8);
                    }
                }
                if (cw) {
                    const uint32_t cx = sb + SM_BX + (rank * 2 + pp) * 512 + lane * 16;
                    st_async_v4(cx, bars + BAR_CX * 8, 0, s[0], s[1], s[2], s[3]); st_async_v4(cx, bars + BAR_CX * 8, 1, s[4], s[5], s[6], s[7]);
                    if (wa == 1) {
                        mbar_wait(bars + BAR_CX * 8, 0);
                        const uint32_t a = sb + SM_BX + lane * 16;
                        const float4 a0 = lds_f4(a), a1 = lds_f4(a + 512), a2 = lds_f4(a + 1024), a3 = lds_f4(a + 1536);
                        st_relaxed_v4(&sc->cs[g][G][rank][lane], make_uint4(tagf((a0.x + a1.x) + (a2.x + a3.x), tag), __float_as_uint((a0.y + a1.y) + (a2.y + a3.y)),
                                                                            __float_as_uint((a0.z + a1.z) + (a2.z + a3.z)), __float_as_uint((a0.w + a1.w) + (a2.w + a3.w))));
                        if (lane == 0) TL(18);
#pragma unroll 1
                        for (int i = lane; i < 140; i += 32) sts_v4(sb + SM_BX + i * 16, make_uint4(0, 0, 0, 0));
                    }
                    bar_sync<7, 64>();
                    uint4 v[8];
#pragma unroll
                    for (int j = 0; j < 8; j++) v[j].x = tag - 1;
                    while (true) {
                        unsigned bad = 0;
#pragma unroll
                        for (int j = 0; j < 8; j++) if ((v[j].x ^ tag) & 15) v[j] = ld_relaxed_v4(&sc->cs[g][j][pp][l]);
                        __syncwarp();
#pragma unroll
                        for (int j = 0; j < 8; j++) bad |= v[j].x ^ tag;
                        if (__all_sync(0xffffffffu, (bad & 15) == 0)) break;
                        spin_guard(spins);
                    }
#pragma unroll
                    for (int e = 0; e < 4; e++) {
                        s[e] = 0.f;
#pragma unroll
                        for (int j = 0; j < 8; j++) s[e] += __uint_as_float((&v[j].x)[e]);
                    }
#pragma unroll
                    for (int j = 0; j < 3; j++) {
                        const int row = 3 * part + j;
                        const uint32_t o0 = pack_bf16(s[0], s[1]), o1 = pack_bf16(s[2], s[3]);
                        s[0] -= bf_lo(o0); s[1] -= bf_hi(o0); s[2] -= bf_lo(o1); s[3] -= bf_hi(o1);
                        sts_f2(sb + SM_BX + pp * 8 + (l < 24 ? row * 128 + (((l ^ row) & 7) << 4) : 1792 + row * 32 + (((l ^ (row >> 2)) & 1) << 4)), __uint_as_float(o0), __uint_as_float(o1));
                    }
                    asm volatile("fence.proxy.async.shared::cta;" ::: "memory");
                    __syncwarp();
                    if (lane == 0) { mbar_arrive(bars + BAR_CS * 8); TL(25); }
                } else {
#pragma unroll
                    for (int e = 0; e < 3; e++) s[e] = ((lane & 4) ? s[4 + e] : s[e]) + shfl_x((lane & 4) ? s[e] : s[4 + e], 4);
#pragma unroll
                    for (int o = 1; o < 4; o <<= 1) {
#pragma unroll
                        for (int e = 0; e < 3; e++) s[e] += shfl_x(s[e], o);
                    }
                    const uint32_t sa = sb + SM_GT + pp * 128 + r * 16;
                    if (aside) {
                        sts_f4(sa, s[0], s[1], s[2], 0.f); asm volatile("bar.arrive 6, 128;" ::: "memory");
                    }
                    else {
                        bar_sync<6, 128>();
                        const float4 o = lds_f4(sa);
                        const int row = 8 * g + ri + (lane & 4);
                        const float mean = (s[0] + o.x) * (1.0f / DM);
                        const float sd = sqrt_approx(bfr(bfr(fmaxf(fmaf(-mean, mean, (s[1] + o.y) * (1.0f / DM)), 0.f)) + 1e-5f));
                        if (c == 0) st_relaxed_v2(&sc->rowinfo[m][pp][row], pack_bf16(mean, sd), tagf(s[2] + o.z, tag));
                        if (wa == 3 && lane == 0) TL(22);
                    }
                    if (!aside) {
                        const uint4* r0 = reinterpret_cast<const uint4*>(&sc->rowinfo[m][pp][0]);
                        uint4 a, b;
                        while (true) {
                            __nanosleep(POLL_NS);
                            a = ld_relaxed_v4(r0 + lane); b = ld_relaxed_v4(r0 + (m > 0 ? 28 - 64 : 0) + c);
                            if (__all_sync(0xffffffffu, (((a.y ^ tag) | (a.w ^ tag) | (b.y ^ tag) | (b.w ^ tag)) & 15) == 0)) break;
                            spin_guard(spins);
                        }
                        sts_f4(sb + SM_ST + (pp * 72 + 8 + 2 * lane) * 8, bf_lo(a.x), rcp(bf_hi(a.x)), bf_lo(a.z), rcp(bf_hi(a.z)));
                        if (lane < 4) sts_f4(sb + SM_ST + (pp * 72 + 2 * lane) * 8, bf_lo(b.x), rcp(bf_hi(b.x)), bf_lo(b.z), rcp(bf_hi(b.z)));
                        __syncwarp();
                        if (lane == 0) { mbar_arrive(bars + BAR_CS * 8); if (pp == 0) TL(24); }
                    }
                }
            }
            if (wa == 6) {
                if (MSGW == 6) while (ld_relaxed_u32(&sc->open[g >> 1][0]) != tag) spin_guard(spins);
                const int r = lane >> 1;
                mbar_wait(bars + (BAR_AE + JL - 1) * 8, 0); mbar_wait(bars + (BAR_FA + 2) * 8, 1); mbar_wait(bars + (BAR_EMPTY + 2) * 8, 1);
#pragma unroll 1
                for (int i = 0; i < 8; i++) {
                    const __nv_bfloat16* src = wo + (i * 80 + r) * DM + ct + (lane & 1) * 8;
                    const uint32_t dst = sb + SM_WT + (i & 1) * 10240 + r * 128 + ((((i & 6) + (lane & 1)) ^ (r & 7)) << 4);
#pragma unroll
                    for (int t = 0; t < 5; t++) cp_async16(dst + t * 2048, src + t * 16 * DM);
                    __nanosleep(TAIL_NS);
                }
                if (MSGW == 6) FETCH_MSG();
                asm volatile("cp.async.wait_all;" ::: "memory");
                asm volatile("fence.proxy.async.shared::cta;" ::: "memory");
                __syncwarp();
                if (lane == 0) { mbar_arrive(bars + BAR_WO * 8); TL(19); }
                GATHER(2);
                return;
            }
            if (moe) {
                const int krow = (lane >> 4) * 8 + (lane & 7), ch = (lane >> 3) & 1;
                const uint32_t wp = sb + SM_MW + (wa - 1) * 1024 + krow * 64 + ((ch ^ (krow >> 1)) & 3) * 16;
                const uint32_t xa = sb + SM_XSEL + (lane & 1) * 1296 + ch * 16 + (wa - 1) * 32 + (lane >> 4) * 160;
                uint32_t a[NPRE][4];
                mbar_wait(bars + BAR_GW * 8, 0);
#pragma unroll
                for (int i = 0; i < NPRE; i++)
                    ldsm4t(((wp + (i >> 1) * 5120) ^ ((i & 1) * 32)) + (i >= PRE_D ? a[i - PRE_D][0] & roles.zero : 0u), a[i]);
                if (NPRE == 12 && lane == 0) mbar_arrive(bars + BAR_OE * 8 + (a[NPRE - 1][0] & roles.zero));
                float d[2][4];
#pragma unroll
                for (int e = 0; e < 8; e++) d[e >> 2][e & 3] = 0.f;
                mbar_wait(bars + BAR_SEL * 8, 0);
                mbar_wait(bars + BAR_GI * 8, 0);
                if (ta == 32) TL(26);
#pragma unroll
                for (int i = 0; i < 8; i += 2) {
                    uint32_t b[4];
                    ldsm4(xa + i * 160, b[0], b[1], b[2], b[3]);
#pragma unroll
                    for (int e = 0; e < 4; e++) {
                        uint32_t (&f)[4] = a[(2 * i + e) % NPRE];
                        mma16(d[e & 1], f[0], f[1], f[2], f[3], b[e & 2], b[(e & 2) + 1]);
                        if (2 * i + e < 16 - NPRE) ldsm4t((wp + (i + (e >> 1) + NPRE / 2 == 7 ? SM_G7 - SM_MW : (i + (e >> 1) + NPRE / 2) * 5120)) ^ ((e & 1) * 32), f);
                    }
                }
                {
                    const float u0 = (c & 2) ? ((c & 1) ? d[1][2] : d[1][0]) : ((c & 1) ? d[0][2] : d[0][0]);
                    const float u1 = (c & 2) ? ((c & 1) ? d[1][3] : d[1][1]) : ((c & 1) ? d[0][3] : d[0][1]);
                    const uint32_t dst = sb + SM_BX + (rank * 5 + wa - 1) * 256 + (c * 8 + r) * 8;
                    mbar_wait(bars + BAR_PG * 8, 0);
                    st_async_v2(dst, bars + BAR_PX * 8, 0, u0, u1); st_async_v2(dst, bars + BAR_PX * 8, 1, u0, u1);
                }
                if (wa >= 2) {
                    mbar_wait(bars + BAR_DW * 8, 0);
#pragma unroll
                    for (int b = 0; b < 5; b++) {
                        const int nb = (wa - 2) * 5 + b;
                        const uint32_t dp = sb + SM_DW + (nb >> 2) * 4096 + krow * 128 + ((((nb & 3) * 2 + ch) ^ (krow & 7)) << 4);
                        ldsm4t(dp, a[2 * b]); ldsm4t(dp + 2048, a[2 * b + 1]);
                    }
                } else {
                    mbar_wait(bars + BAR_PX * 8, 0);
                    if (lane == 0) { if (NPRE != 12) mbar_arrive(bars + BAR_OE * 8); TL(27); }
                    float2 gs = make_float2(0.f, 0.f), us = gs;
#pragma unroll
                    for (int e = 0; e < 5; e++) {
                        const float2 u = lds_f2(sb + SM_BX + e * 256 + lane * 8), v = lds_f2(sb + SM_BX + 1280 + e * 256 + lane * 8);
                        gs.x += u.x; gs.y += u.y; us.x += v.x; us.y += v.y;
                    }
                    const uint32_t g2 = pack_bf16(gs.x, gs.y);
                    const uint32_t h2 = hmul2(pack_bf16(bf_lo(g2) * sigmoid_f(bf_lo(g2)), bf_hi(g2) * sigmoid_f(bf_hi(g2))), pack_bf16(us.x, us.y));
                    sts_u16(sb + SM_H + lane * 2, h2); sts_u16(sb + SM_H + 64 + lane * 2, h2 >> 16);
                }
                bar_sync<3, 160>();
                if (wa >= 2) {
                    uint32_t hb[4];
                    ldsm4(sb + SM_H + (lane & 1) * 64 + (lane >> 3) * 16, hb[0], hb[1], hb[2], hb[3]);
                    float yv[5];
#pragma unroll
                    for (int b = 0; b < 5; b++) {
                        float o[4] = {0.f, 0.f, 0.f, 0.f};
                        mma16(o, a[2 * b][0], a[2 * b][1], a[2 * b][2], a[2 * b][3], hb[0], hb[1]);
                        mma16(o, a[2 * b + 1][0], a[2 * b + 1][1], a[2 * b + 1][2], a[2 * b + 1][3], hb[2], hb[3]);
                        yv[b] = (c & 2) ? ((c & 1) ? o[3] : o[2]) : ((c & 1) ? o[1] : o[0]);
                    }
                    uint4* const dst = &sc->yp[rank * 4 + wa - 2][mi][0];
                    {
                    uint32_t u[5];
#pragma unroll
                    for (int e = 0; e < 5; e++) u[e] = __float_as_uint(yv[e]) + 128;
                    st_relaxed_v4(dst + lane, make_uint4(__byte_perm(u[0], u[4], 0x3215), __byte_perm(u[1], u[4], 0x3216), __byte_perm(u[2], u[4], 0x3217), __byte_perm(u[3], tag, 0x3214))); }
                    if (lane == 0) mbar_arrive(bars + (BAR_OE + 1) * 8);
                    if (wa == 3 && lane == 0) TL(28);
                }
            } else if (lane == 0) { if (wa > 1) mbar_arrive(bars + (BAR_OE + 1) * 8); if (wa == 1 || NPRE == 12) mbar_arrive(bars + BAR_OE * 8); }
            if (wa == 1) {
                mbar_wait(bars + BAR_SEL * 8, 0);
                const uint2 sel = lds_v2(sb + SM_TOP);
                if ((sel.x >> 7) == m || (sel.y >> 7) == m) {
                    uint4 v;
                    mbar_wait(bars + BAR_OF * 8, 0);
                    do { if (GT_NS) __nanosleep(GT_NS); v = ld_relaxed_v4(&box->gt[g & 1][min(lane, 19)]); spin_guard(spins); } while (__any_sync(0xffffffffu, v.x == EMPTY_WORD));
                    sts_v4(sb + SM_GT + min(lane, 19) * 16, v);
                    __syncwarp();
                    if (lane == 0) TL(30);
                }
                if (lane == 0) { mbar_arrive(bars + BAR_Y * 8); st_relaxed_u32(&sc->epoch[cta * 32], tag); }
            }
        }
    } else {
        asm volatile("setmaxnreg.inc.sync.aligned.u32 184;");
        const int p = warp >> 2, w = warp & 3, c = lane & 3, r = lane >> 2;
        const uint32_t stb = sb + SM_ST + (p * 72 + w * 16) * 8;
        float acc[120];
#pragma unroll
        for (int i = 0; i < 120; i++) asm volatile("" : "=f"(acc[i]));
        uint32_t xs[5][4];
#pragma unroll
        for (int i = 0; i < 20; i++) asm volatile("" : "=r"(xs[i >> 2][i & 3]));
#define EXT_STEP() do {        \
            mbar_wait(bars + BAR_CS * 8, 0); \
            const uint32_t msk = c == 0 ? 0xffffffffu : (c == 1 ? 0x0000ffffu : 0u); \
            const uint32_t e0 = dup_hi(-lds_f32(stb + (8 + r) * 8)) & msk, e1 = dup_hi(-lds_f32(stb + (16 + r) * 8)) & msk; \
            wg_fence(); \
            wgmma_rs_n48x(acc, e0, e1, 0u, 0u, (((sb + SM_BX + 1792) & 0x3ffffu) >> 4) | ((96u >> 4) << 16)); \
            wgmma_rs_n192x(acc, e0, e1, 0u, 0u, (((sb + SM_BX) & 0x3ffffu) >> 4) | ((384u >> 4) << 16)); \
            wg_commit(); } while (0)
#define EXT_J 4
        cluster_wait();
        {
            const int lr = w * 16 + (lane & 15);
            uint32_t st = __shfl_sync(0xffffffffu, sb + p * 8192 + lr * 128 + (((lr & 7) ^ (lane >> 4)) << 4), lane);
            const bool lead = __shfl_sync(0xffffffffu, tid & 127, lane) == 0;
            uint32_t blo = (((sb + OFF_B) & 0x3ffffu) >> 4) | ((4096u >> 4) << 16);
            const uint32_t tdiff = (12288u >> 4) + ((1024u >> 4) << 16) - ((4096u >> 4) << 16);
            uint32_t xo[5]; unsigned long long xm = 0;
#pragma unroll
            for (int t = 0; t < 5; t++) {
                const int ks = 5 * g + (t < 4 ? t + odd : 4 - 4 * odd), kq = (ks >> 2) - (k0 >> 6);
                xo[t] = __shfl_sync(0xffffffffu, (ks & 3) << 5, lane);
                xm |= 1ull << (5 * (kq < 0 ? kq + 10 : kq) + t);
            }
#define PD 1
            asm volatile("" : "+l"(xm));
            sched_fence();
            uint32_t af[4][4];
            mbar_wait(bars + BAR_FA * 8, 0);
            ldsm4(st, af[0][0], af[0][1], af[0][2], af[0][3]);
            if (PD == 2) ldsm4(st ^ 32, af[1][0], af[1][1], af[1][2], af[1][3]);
#pragma unroll
            for (int kt = 0; kt < 10; kt++) {
#pragma unroll
                for (int j = 0; j < 4; j++) {
                    uint32_t (&nx)[4] = af[(j + PD) & 3];
                    if (j == 0) {
                        mbar_wait(bars + (BAR_FULL + (kt & 3)) * 8, (kt >> 2) & 1);
                    }
                    if (j == 4 - PD && kt < 9) {
                        st += (kt & 3) == 0 ? 3 * STAGE : -STAGE;
                        mbar_wait(bars + (BAR_FA + ((kt + 1) & 3)) * 8, ((kt + 1) >> 2) & 1);
                    }
                    if (G1S && j == (40 - G1S) % 4 && kt == (40 - G1S) / 4 && p == 1) bar_sync<8, 256>();
                    ldsm4(st ^ (((j + PD) & 3) << 5), nx[0], nx[1], nx[2], nx[3]);
                    wg_fence();
                    const uint32_t sd = j ? 1u : (uint32_t)kt;
                    wgmma_rs_n48(acc, af[j][0], af[j][1], af[j][2], af[j][3], blo + tdiff + (j >> 1) * (B_HALF >> 4) + (j & 1) * 32, sd);
                    wgmma_rs_n192(acc, af[j][0], af[j][1], af[j][2], af[j][3], blo + (j >> 1) * (B_HALF >> 4) + (j & 1) * 128, sd);
                    wg_commit();
#define WD 2
                    wg_wait<WD>();
                    if (j == WD - 1 && kt > 0 && lead) mbar_arrive_both(bars + (BAR_EMPTY + ((kt - 1) & 3)) * 8);
                    if (j == EXT_J && kt == 9) EXT_STEP();
                    if (j == XJ) {
                        if (xm & 31) {
#pragma unroll
                            for (int t = 0; t < 5; t++) ldsm4_if((xm >> t) & 1, st ^ xo[t], xs[t]);
                        }
                        xm >>= 5;
                    }
                }
                blo += (kt & 3) == 0 ? 3 * (STAGE >> 4) : -(STAGE >> 4);
            }
        }
        if (G1S && p == 0) asm volatile("bar.arrive 8, 256;" ::: "memory");
        if (EXT_J > 3) EXT_STEP();
        if (tid == 0) TL(10);
        const float2 st0 = lds_f2(stb + (8 + r) * 8), st1 = lds_f2(stb + (16 + r) * 8);
        const float rs0 = st0.y, rs1 = st1.y;
        const uint4 sP = lds_v4(stb + (2 * c) * 8), sB = lds_v4(stb + (8 + 2 * c) * 8), sC = lds_v4(stb + (16 + 2 * c) * 8);
        const bool up0 = 2 * c > r, up1 = 2 * c + 1 > r;
        float k00 = __uint_as_float(up0 ? sP.y : sB.y), k01 = __uint_as_float(up1 ? sP.w : sB.w);
        float k10 = __uint_as_float(up0 ? sB.y : sC.y), k11 = __uint_as_float(up1 ? sB.w : sC.w);
        const float sc2 = 0.22360679774997896f * 1.4426950408889634f;
        const uint32_t exs = __shfl_sync(0xffffffffu, sb + SM_EX + p * 8192 + w * 2560 + lane * 16, lane), exr = exs - (w ? 2560 : 0);
        uint4* hg = &sc->halo[m * 8 + g - (w ? 0 : 8)][p * 160 + lane];
        asm volatile("" : "+l"(hg));
        mbar_wait(bars + BAR_RS * 8, 0);
        if (p == 0) bar_sync<1, 128>(); else bar_sync<2, 128>();
        sched_fence();
        wg_wait<0>();
        if ((tid & 127) == 0) TL(2 + p);
        if (tid == 64) GT(59);
        uint32_t Q[10][2], K[10][2], V[10][2], Kp[10], Vp[10];
        uint4 rcv[5];
#define BX(h) (5 * ((h) >> 1) + 3 * ((h) & 1))
#define BZ(h) (5 * ((h) >> 1) + 2)
        float fa[4], fb[4], l[4][2];
        uint32_t qz[4][2], eh[4], ph[4];
        const bool first = (m == 0 && w == 0), far = (m > 0 && w == 0);
#define AV 20
#define MSK(a, b) hmul2(a, b)
        const uint32_t mup = (up0 ? 0x00003f80u : 0u) | (up1 ? 0x3f800000u : 0u), mdn = mup ^ 0x3f803f80u;
        const uint32_t qlo = c < 2;
#define SEND() do { \
            st_halo(w == 3, hg, exs, K[0][1], K[1][1], K[3][1], K[4][1]); st_halo(w == 3, hg + 32, exs + 512, K[5][1], K[6][1], K[8][1], K[9][1]); \
            st_halo(w == 3, hg + 64, exs + 1024, K[2][1], K[7][1], V[0][1], V[1][1]); st_halo(w == 3, hg + 96, exs + 1536, V[2][1], V[3][1], V[4][1], V[5][1]); \
            st_halo(w == 3, hg + 128, exs + 2048, V[6][1], V[7][1], V[8][1], V[9][1]); G1_DONE(); } while (0)
#define RECV() do { bar_sync_id(1 + p, 128); \
            if (AV & 2) { _Pragma("unroll") for (int i = 0; i < 5; i++) rcv[i] = ld_halo(far, hg + i * 32, exr + i * 512); } \
            else if (far && !(AV & 16)) { _Pragma("unroll") for (int i = 0; i < 5; i++) rcv[i] = ld_relaxed_v4(hg + i * 32); } \
            else { _Pragma("unroll") for (int i = 0; i < 5; i++) rcv[i] = lds_v4(exr + i * 512); } } while (0)
#define OWN_KEYS(ODD) do { \
            asm volatile("" : "+f"(k00), "+f"(k01), "+f"(k10), "+f"(k11) :: "memory"); \
            const float f00 = rs0 * k00 * sc2, f01 = rs0 * k01 * sc2, f10 = rs1 * k10 * sc2, f11 = rs1 * k11 * sc2; \
            fa[0] = up0 ? f00 : 0.f; fa[1] = up1 ? f01 : 0.f; fa[2] = up0 ? f10 : 0.f; fa[3] = up1 ? f11 : 0.f; \
            fb[0] = f00 - fa[0]; fb[1] = f01 - fa[1]; fb[2] = f10 - fa[2]; fb[3] = f11 - fa[3]; \
            const float b00 = (first && up0) ? -1e30f : 0.f, b01 = (first && up1) ? -1e30f : 0.f; \
            if (!(AV & 4)) pack_q<ODD>(acc, Q); \
            pack_kv<ODD, 0>(acc, K, V); \
            if (AV & 16) { _Pragma("unroll") for (int b = 0; b < 10; b++) asm volatile("" : "+r"(K[b][0]), "+r"(V[b][0]) :: "memory"); \
                _Pragma("unroll") for (int i = 0; i < 5; i++) ldg_if(far, hg + i * 32, rcv[i]); if (AV & 32) sched_fence(); } \
            _Pragma("unroll") for (int h = 0; h < 4; h++) { \
                const int bx = BX(h), by = bx + 1, bz = BZ(h); \
                if (h & 1) { qz[h][0] = Q[bz][0] - qz[h & 2][0]; qz[h][1] = Q[bz][1] - qz[h & 2][1]; } \
                else { qz[h][0] = imul(Q[bz][0], qlo); qz[h][1] = imul(Q[bz][1], qlo); } \
                float sm_[4] = {0.f, 0.f, 0.f, 0.f}, sn[4] = {0.f, 0.f, 0.f, 0.f}; \
                mma16(sm_, Q[bx][0], Q[bx][1], Q[by][0], Q[by][1], K[bx][0], K[by][0]); \
                mma16(sn, Q[bx][0], Q[bx][1], Q[by][0], Q[by][1], K[bx][1], K[by][1]); \
                mma8(sm_, qz[h][0], qz[h][1], K[bz][0]); mma8(sn, qz[h][0], qz[h][1], K[bz][1]); \
                l[h][0] = fmaf(sm_[0], fb[0], b00); l[h][1] = fmaf(sm_[1], fb[1], b01); \
                const float l2 = fmaf(sm_[2], fa[2], sn[2] * fb[2]), l3 = fmaf(sm_[3], fa[3], sn[3] * fb[3]); \
                float m1 = fmaxf(l2, l3); \
                m1 = fmaxf(m1, shfl_x(m1, 1)); m1 = fmaxf(m1, shfl_x(m1, 2)); \
                const float e2 = ex2(l2 - m1), e3 = ex2(l3 - m1); \
                eh[h] = pack_bf16(e2, e3); ph[h] = pack_bf16(e2 * k10, e3 * k11); \
                asm volatile("" : "+r"(eh[h]), "+r"(ph[h]) :: "memory"); \
            } } while (0)
#define PACK_Q_EARLY(ODD) do { if (AV & 4) { sched_fence(); pack_q<ODD>(acc, Q); _Pragma("unroll") for (int b = 0; b < 10; b++) asm volatile("" : "+r"(Q[b][0]), "+r"(Q[b][1]) :: "memory"); } } while (0)
        if (AV & 1) {
            if (odd) { pack_kv<1, 1>(acc, K, V); SEND(); PACK_Q_EARLY(1); RECV(); if (AV & 8) sched_fence(); OWN_KEYS(1); }
            else { pack_kv<0, 1>(acc, K, V); SEND(); PACK_Q_EARLY(0); RECV(); if (AV & 8) sched_fence(); OWN_KEYS(0); }
        } else {
            if (odd) { pack_kv<1, 1>(acc, K, V); SEND(); PACK_Q_EARLY(1); } else { pack_kv<0, 1>(acc, K, V); SEND(); PACK_Q_EARLY(0); }
            ATS(1);
            RECV();
            ATS(2);
            if (odd) OWN_KEYS(1); else OWN_KEYS(0);
        }
        ATS(3);
        if (tid == 0) TL(11);
        if (far) {
            unsigned spins = 0;
            while (__any_sync(0xffffffffu, max(max(max(rcv[0].x, rcv[1].x), max(rcv[2].x, rcv[3].x)), rcv[4].x) == EMPTY_WORD) && ++spins < SPIN_MAX) {
#pragma unroll
                for (int i = 0; i < 5; i++) rcv[i] = ld_relaxed_v4(hg + i * 32);
            }
        }
        Kp[0] = rcv[0].x; Kp[1] = rcv[0].y; Kp[3] = rcv[0].z; Kp[4] = rcv[0].w; Kp[5] = rcv[1].x; Kp[6] = rcv[1].y; Kp[8] = rcv[1].z; Kp[9] = rcv[1].w;
        Kp[2] = rcv[2].x; Kp[7] = rcv[2].y; Vp[0] = rcv[2].z; Vp[1] = rcv[2].w; Vp[2] = rcv[3].x; Vp[3] = rcv[3].y; Vp[4] = rcv[3].z; Vp[5] = rcv[3].w;
        Vp[6] = rcv[4].x; Vp[7] = rcv[4].y; Vp[8] = rcv[4].z; Vp[9] = rcv[4].w;
        ATS(4);
        if (tid == 0) TL(4);
        if (tid == 128) TL(5);
        uint32_t* ob = reinterpret_cast<uint32_t*>(&sc->o[m][0][g][warp * 32]) + lane;
        uint32_t of[10][2];
#define PUBLISH(t) do { st_relaxed_u32(ob + (t) * 8192, of[2 * (t)][0]); st_relaxed_u32(ob + (t) * 8192 + 32, of[2 * (t) + 1][0]); \
            st_relaxed_u32(ob + (t) * 8192 + 64, of[2 * (t)][1]); st_relaxed_u32(ob + (t) * 8192 + 96, of[2 * (t) + 1][1]); \
            if (((t) == 1 || (t) == 2) && lane == 0) mbar_arrive(bars + (BAR_PA + (t)) * 8); } while (0)
#define ANNOUNCE(n) do { if (ANP == (n)) { if (lane == 0) mbar_arrive(bars + BAR_AN * 8); } } while (0)
#define FRONT(h) do { \
            float sp[4] = {0.f, 0.f, 0.f, 0.f}; \
            mma16(sp, Q[BX(h)][0], Q[BX(h)][1], Q[BX(h) + 1][0], Q[BX(h) + 1][1], Kp[BX(h)], Kp[BX(h) + 1]); \
            mma8(sp, qz[h][0], qz[h][1], Kp[BZ(h)]); \
            l[h][0] = fmaf(sp[0], fa[0], l[h][0]); l[h][1] = fmaf(sp[1], fa[1], l[h][1]); \
            float m0 = fmaxf(l[h][0], l[h][1]); \
            m0 = fmaxf(m0, shfl_x(m0, 1)); m0 = fmaxf(m0, shfl_x(m0, 2)); \
            l[h][0] -= m0; l[h][1] -= m0; } while (0)
#define BACK(h) do { \
            const float e0 = ex2(l[h][0]), e1 = ex2(l[h][1]); \
            float sum[4] = {0.f, 0.f, 0.f, 0.f}, O[3][4]; \
            mma8(sum, pack_bf16(e0, e1), eh[h], 0x3f803f80u); \
            const uint32_t pl = pack_bf16(e0 * k00, e1 * k01); \
            const uint32_t a0 = MSK(pl, mdn), a1 = MSK(ph[h], mup), a3 = MSK(ph[h], mdn), ap = MSK(pl, mup); \
            const float i0 = rcp(sum[0]), i1 = rcp(sum[2]); \
            _Pragma("unroll") for (int b = 0; b < 3; b++) { \
                const int bb = b < 2 ? BX(h) + b : BZ(h); \
                O[b][0] = O[b][1] = O[b][2] = O[b][3] = 0.f; \
                mma16(O[b], a0, a1, 0u, a3, V[bb][0], V[bb][1]); mma8(O[b], ap, 0u, Vp[bb]); \
                const uint32_t o0 = pack_bf16(O[b][0] * i0, O[b][1] * i0), o1 = pack_bf16(O[b][2] * i1, O[b][3] * i1); \
                of[bb][0] = (b == 2 && ((h) & 1) && c < 2) ? of[bb][0] : o0; of[bb][1] = (b == 2 && ((h) & 1) && c < 2) ? of[bb][1] : o1; \
            } } while (0)
#define HOLD_L(h) asm volatile("" : "+f"(l[h][0]), "+f"(l[h][1]) :: "memory")
#define HOLD_K(h) asm volatile("" : "+r"(Kp[BX(h)]) :: "memory")
#define PA() do { if (tid == 0) TL(6); if (tid == 128) TL(8); } while (0)
        ANNOUNCE(0);
        FRONT(0); FRONT(1); if (ANP == 1) HOLD_L(0); ANNOUNCE(1); BACK(0); ANNOUNCE(2); PUBLISH(0); ANNOUNCE(3); PA(); sched_fence(); HOLD_L(1); HOLD_K(2); HOLD_K(3); FRONT(2); FRONT(3); BACK(1); PUBLISH(1); sched_fence(); HOLD_L(2); HOLD_L(3); BACK(2); PUBLISH(2); BACK(3);
        if (tid == 0) TL(7);
        if (tid == 128) TL(9);
#define TRK 4
        float acc2[40];
#pragma unroll
        for (int i = 0; i < 40; i++) asm volatile("" : "=f"(acc2[i]));
        uint32_t gate[5][4];
        if ((TRK <= 1 || TRK == 4) && SPLIT != 3) PUBLISH(2);
        if (TRK == 0) { PUBLISH(3); PUBLISH(4); }
        const float2 su0 = lds_f2(stb + (8 + r) * 8), su1 = lds_f2(stb + (16 + r) * 8);
        const float rh0 = bfr(0.5f * su0.y), rh1 = bfr(0.5f * su1.y);
        const uint32_t gm[2] = {dup_hi(su0.x), dup_hi(su1.x)}, gh[2] = {dup_hi(rh0), dup_hi(rh1)};
        const uint32_t gl[2] = {pack_bf16(0.5f * su0.y - rh0, 0.5f * su0.y - rh0), pack_bf16(0.5f * su1.y - rh1, 0.5f * su1.y - rh1)};
        mbar_wait(bars + BAR_WO * 8, 0);
        bar_sync<4, 256>();
        if (tid == 0) TL(13);
        const uint32_t wlo = ((sb + SM_WO) & 0x3ffffu) >> 4, alo = (((sb + p * 2048) & 0x3ffffu) >> 4) | (8u << 16);
        uint32_t wd_[8];
#pragma unroll
        for (int i = 0; i < 8; i++) wd_[i] = wlo + (7 - i) * 640 + (((SM_WT - SM_WO - (7 - i) * 10240 + (SRC(i) & 1) * 10240 + (SRC(i) >> 1) * 32) >> 4) << 16);
        wg_fence();
#pragma unroll
        for (int t = 0; t < 5; t++) wgmma_rs_n80(acc2, of[2 * t][0], of[2 * t][1], of[2 * t + 1][0], of[2 * t + 1][1], wd_[0] + t * 128, t != 0);
        wg_commit();
#define NG0 4
#define GATES(t) do { _Pragma("unroll") for (int e = 0; e < 4; e++) {        \
                const uint32_t d = hsub2(xs[t][e], gm[e & 1]), h2 = hfma2(d, gh[e & 1], hmul2(d, gl[e & 1]));        \
                const float a = bf_lo(h2), b = bf_hi(h2); \
                gate[t][e] = pack_bf16(fmaf(a, tanh_f(a), a), fmaf(b, tanh_f(b), b)); \
                asm volatile("" : "+r"(gate[t][e]) :: "memory"); } } while (0)
        GATES(0);
        if (TRK == 4) { sched_fence(); PUBLISH(3); }
        if (TRK && TRK < 4) {
            mbar_wait(bars + BAR_GI * 8, 0);
            if (TRK >= 2 && SPLIT != 3) PUBLISH(2);
            if (TRK <= 2) { PUBLISH(3); PUBLISH(4); }
        }
#pragma unroll
        for (int t = 1; t < NG0; t++) GATES(t);
        if (TRK == 4) { sched_fence(); PUBLISH(4); }
        if (WO_L < 8) mbar_wait(bars + BAR_W2 * 8, 0);
        if (tid == 0) TL(12);
#pragma unroll
        for (int t = 0; t < 5; t++) {
            const uint32_t ad = alo + ((t == 2 ? SM_O2 : ((t == 0 || t == 3) ? SM_O0 : SM_O1)) >> 4);
            mbar_spin(bars + (BAR_OF + t) * 8, 0);
            if (STAG < 5 && t == STAG && p == 1) bar_sync<5, 256>();
            if (TRK == 3 && t == 0) { PUBLISH(3); PUBLISH(4); }
            wg_fence();
#pragma unroll
            for (int i = 0; i < 7; i++) {
                wgmma_ss_n80(acc2, ad + i * 256, wd_[i + 1] + t * 128);
                if (i == 0 && (t == 1 || t == 2)) {
                    wg_commit(); wg_wait<1>();
                    if ((tid & 127) == 0) mbar_arrive(bars + (BAR_OE + t + 1) * 8);
                }
                if (STAG < 5 && i == 4 && t == 4 && p == 0) asm volatile("bar.arrive 5, 256;" ::: "memory");
            }
            wg_commit();
            if (t + NG0 < 5) GATES(t + NG0);
        }
        const int wrow = m * 128 + 32 * w + p;
        {
            mbar_wait(bars + BAR_SEL * 8, 0);
            const uint2 sel = lds_v2(sb + SM_TOP);
            const unsigned d0 = sel.x - wrow, d1 = sel.y - wrow;
            if ((d0 & ~30u) == 0 || (d1 & ~30u) == 0) {
                mbar_wait(bars + BAR_Y * 8, 0);
#pragma unroll
                for (int h = 0; h < 2; h++) {
                    const unsigned me = 2 * r + 16 * h;
                    if (d0 == me || d1 == me) {
#pragma unroll
                        for (int t = 0; t < 5; t++) {
                            const uint32_t a = sb + SM_GT + (d0 == me ? 0 : 160) + (t < 4 ? t + odd : 4 - 4 * odd) * 32 + c * 4;
                            gate[t][h] = lds_u32(a); gate[t][2 + h] = lds_u32(a + 16);
                        }
                    }
                }
                __syncwarp();
            }
        }
        const uint32_t ssb = sb + (warp < 6 ? SM_EX : SM_G7 - 6 * 2560) + warp * 2560;
        const uint32_t laddr = ssb + (lane & 15) * 160 + (lane >> 4) * 16;
        wg_wait<0>();
        if (tid == 0) TL(1);
        if (tid == 128) TL(14);
        if (__any_sync(0xffffffffu, acc2[0] != acc2[0] || acc2[2] != acc2[2])) {
#pragma unroll
            for (int i = 0; i < 40; i++) acc2[i] = 0.f;
            const int krow = lane & 15;
#pragma unroll 1
            for (int ks = 0; ks < 40; ks++) {
                const int i = ks / 5;
                const uint32_t* src = ob + (ks - 5 * i) * 8192 + (SRC(i) - g) * 1024;
                uint32_t a0, a1, a2, a3; unsigned spins = 0;
                do { a0 = ld_relaxed_u32(src); a2 = ld_relaxed_u32(src + 32); a1 = ld_relaxed_u32(src + 64); a3 = ld_relaxed_u32(src + 96); }
                while (__any_sync(0xffffffffu, max(max(a0, a1), max(a2, a3)) == EMPTY_WORD) && ++spins < SPIN_MAX);
#pragma unroll
                for (int nb = 0; nb < 5; nb++) {
                    uint32_t b[4];
                    ldsm4t(sb + (nb < 4 ? SM_WO + (35 + ks - 10 * i) * 2048 : SM_WT + ((SRC(i) & 1) * 5 + ks - 5 * i) * 2048) + krow * 128 + (((2 * (nb < 4 ? nb : SRC(i) >> 1) + (lane >> 4)) ^ (krow & 7)) << 4), b);
                    mma16(*reinterpret_cast<float (*)[4]>(&acc2[8 * nb]), a0, a1, a2, a3, b[0], b[1]);
                    mma16(*reinterpret_cast<float (*)[4]>(&acc2[8 * nb + 4]), a0, a1, a2, a3, b[2], b[3]);
                }
            }
        }
#pragma unroll
        for (int t = 0; t < 5; t++) {
            uint32_t o[4];
#pragma unroll
            for (int e = 0; e < 4; e++) o[e] = hadd2(xs[t][e], hmul2(pack_bf16(acc2[8 * t + 2 * e], acc2[8 * t + 2 * e + 1]), gate[t][e]));
            stsm4(laddr + (t < 4 ? t + odd : 4 - 4 * odd) * 32, o[0], o[1], o[2], o[3]);
        }
        asm volatile("fence.proxy.async.shared::cta;" ::: "memory");
        __syncwarp();
        if (elect_one()) tma3d_store(&tm_o, ssb, g * 80, m * 64 + w * 16, p);
    }
}

typedef CUresult (*EncodeFn)(CUtensorMap*, CUtensorMapDataType, cuuint32_t, void*, const cuuint64_t*, const cuuint64_t*, const cuuint32_t*,
                             const cuuint32_t*, CUtensorMapInterleave, CUtensorMapSwizzle, CUtensorMapL2promotion, CUtensorMapFloatOOBfill);

static void encode(EncodeFn enc, CUtensorMap* tm, const void* ptr, int rank, uint64_t d0, uint64_t d1, uint64_t d2, uint64_t s1, uint64_t s2,
                   uint32_t b0, uint32_t b1, uint32_t b2, CUtensorMapSwizzle swz) {
    cuuint64_t dims[3] = {d0, d1, d2}, strides[2] = {s1, s2};
    cuuint32_t box[3] = {b0, b1, b2}, es[3] = {1, 1, 1};
    enc(tm, CU_TENSOR_MAP_DATA_TYPE_BFLOAT16, rank, const_cast<void*>(ptr), dims, strides, box, es, CU_TENSOR_MAP_INTERLEAVE_NONE, swz,
        CU_TENSOR_MAP_L2_PROMOTION_L2_128B, CU_TENSOR_MAP_FLOAT_OOB_FILL_NONE);
}

}

extern "C" void kernel_launch(void* const* d_in, const int* in_sizes, int n_in, void* d_out, int out_size) {
    using namespace fk;
    (void)in_sizes; (void)n_in; (void)out_size;
    const __nv_bfloat16* x = (const __nv_bfloat16*)d_in[0];
    const __nv_bfloat16* wqkv = (const __nv_bfloat16*)d_in[1];
    const __nv_bfloat16* wo = (const __nv_bfloat16*)d_in[2];
    const __nv_bfloat16* wr = (const __nv_bfloat16*)d_in[4];
    const __nv_bfloat16* wg = (const __nv_bfloat16*)d_in[5];
    const __nv_bfloat16* wu = (const __nv_bfloat16*)d_in[6];
    const __nv_bfloat16* wd = (const __nv_bfloat16*)d_in[7];
    static EncodeFn enc = nullptr;
    static Scratch* scratch = nullptr;
    static Roles roles; static int by_sm = 0;
    if (!enc) {
        void* fn = nullptr; cudaDriverEntryPointQueryResult qr;
        cudaGetDriverEntryPoint("cuTensorMapEncodeTiled", &fn, cudaEnableDefault, &qr);
        enc = (EncodeFn)fn;
        cudaFuncSetAttribute(fused_kernel, cudaFuncAttributeMaxDynamicSharedMemorySize, SM_TOTAL);
        cudaGetSymbolAddress((void**)&scratch, g_scratch);
        int dev = 0, nsm = 0;
        cudaGetDevice(&dev); cudaDeviceGetAttribute(&nsm, cudaDevAttrMultiProcessorCount, dev);
        by_sm = nsm == NCTA + NIDLE;
        roles.k16 = 0x10000; roles.zero = 0;
        for (int t = 0; t < 66; t++) roles.pair[t] = t < 32 ? (t & 7) * 8 + (t >> 3) : (t < 60 ? (1 + (t - 32) % 7) * 8 + 4 + (t - 32) / 7 : (t < 62 ? t + 4 : t - 58));
    }
    CUtensorMap tx, tw, twt, two, twn, td, tg, tu, to;
    encode(enc, &tx, x, 3, 640, 1024, 2, 2560, 1280, 64, 64, 2, CU_TENSOR_MAP_SWIZZLE_128B);
    encode(enc, &tw, wqkv, 3, 640, 640, 3, 3840, 1280, 64, 32, 3, CU_TENSOR_MAP_SWIZZLE_128B);
    encode(enc, &twt, wqkv, 3, 640, 640, 3, 3840, 1280, 16, 32, 3, CU_TENSOR_MAP_SWIZZLE_32B);
    encode(enc, &two, wo, 2, 640, 640, 1, 1280, 0, 64, 80, 1, CU_TENSOR_MAP_SWIZZLE_128B);
    encode(enc, &twn, wo, 3, 640, 4, 160, 160 * 1280, 1280, 16, 4, 160, CU_TENSOR_MAP_SWIZZLE_NONE);
    encode(enc, &td, wd, 2, 640, 1728, 1, 1280, 0, 64, 32, 1, CU_TENSOR_MAP_SWIZZLE_128B);
    encode(enc, &to, d_out, 3, 640, 1024, 2, 2560, 1280, 80, 16, 1, CU_TENSOR_MAP_SWIZZLE_NONE);
    encode(enc, &tg, wg, 2, 1728, 640, 1, 3456, 0, 32, 80, 1, CU_TENSOR_MAP_SWIZZLE_64B);
    encode(enc, &tu, wu, 2, 1728, 640, 1, 3456, 0, 32, 80, 1, CU_TENSOR_MAP_SWIZZLE_64B);
    fused_kernel<<<NCTA + NIDLE, NTHREADS, SM_TOTAL>>>(scratch, x, wqkv, wo, wr, wd, (__nv_bfloat16*)d_out, by_sm, roles, tx, tw, twt, two, twn, td, tg, tu, to);
}
```
